```python
import torch

def _softmax(x, axis=-1):
    return torch.softmax(x, dim=axis)
def _gelu(x):
    return torch.nn.functional.gelu(x, approximate="tanh")
def _silu(x):
    return torch.nn.functional.silu(x)
def _sigmoid(x):
    return torch.sigmoid(x)
def _layernorm(x, axis=-1, eps=1e-5):
    m = x.mean(dim=axis, keepdim=True)
    v = x.var(dim=axis, keepdim=True, unbiased=False)
    return (x - m) / torch.sqrt(v + eps)
def _scatter_add(tgt, idx, src, axis=0):
    return tgt.clone().index_add_(axis, idx, src)
def _segment_sum(src, seg, n):
    out = torch.zeros((n,) + src.shape[1:], dtype=src.dtype)
    return out.index_add_(0, seg, src)
def _pad(x, pw):
    flat = tuple(v for pair in reversed(pw) for v in pair)
    return torch.nn.functional.pad(x, flat)

kernel_name = 'gated_mix__linear_attn_block__mha_block__prompt'

def setup_inputs():

    _w = (lambda a: (lambda t: t.to(torch.bfloat16) if t.is_floating_point() else t)(torch.as_tensor(a)))
    def _A_setup():
        B, S, D = 1, 2048, 640
        return {
            "x": _w((lambda *s: torch.randn(*s, dtype=torch.bfloat16) * 0.05)(B, S, D)),
            "wqkv": _w((lambda *s: torch.randn(*s, dtype=torch.bfloat16) * 0.8)(D, 3 * D)),
            "wo": _w((lambda *s: torch.randn(*s, dtype=torch.bfloat16) * 0.2)(D, D)),
        }
    _A_in = _A_setup()

    def _B_setup():
        B, S, D, H = 1, 2048, 640, 32
        return {
            "x": _w((lambda *s: torch.randn(*s, dtype=torch.bfloat16) * 0.05)(B, S, D)),
            "wqkv": _w((lambda *s: torch.randn(*s, dtype=torch.bfloat16) * 0.8)(D, 3 * D)),
            "wo": _w((lambda *s: torch.randn(*s, dtype=torch.bfloat16) * 0.05)(D, D)),
        }
    _B_in = _B_setup()

    return {
        "A_x": _A_in["x"],
        "A_wqkv": _A_in["wqkv"],
        "A_wo": _A_in["wo"],
        "B_x": _B_in["x"],
        "B_wqkv": _B_in["wqkv"],
        "B_wo": _B_in["wo"],
        "gate_w": _w((lambda *s: torch.randn(*s, dtype=torch.bfloat16) * 0.05)(640) * 16.0),
    }

def reference(A_x, A_wqkv, A_wo, B_x, B_wqkv, B_wo, gate_w):
    def _A_ref(x, wqkv, wo):
        B, S, D = x.shape
        H = 32; Dh = D // H
        qkv = (lambda x, *d: x.permute(*d))((x @ wqkv).reshape(B, S, 3, H, Dh), 2, 0, 3, 1, 4)
        q, k, v = qkv[0], qkv[1], qkv[2]
        phi = lambda t: torch.where(t > 0, t + 1, torch.exp(t)) + 1e-6
        pq, pk = phi(q), phi(k)
        kv = torch.einsum("bhsd,bhse->bhde", pk, v)
        z = torch.einsum("bhsd->bhd", pk)
        num = torch.einsum("bhqd,bhde->bhqe", pq, kv)
        den = torch.einsum("bhqd,bhd->bhq", pq, z)[..., None] + 1e-6
        o = num / den
        return (lambda x, *d: x.permute(*d))(o, 0, 2, 1, 3).reshape(B, S, D) @ wo

    def _B_ref(x, wqkv, wo):
        B, S, D = x.shape
        H = 32
        Dh = D // H
        qkv = (lambda x, *d: x.permute(*d))((x @ wqkv).reshape(B, S, 3, H, Dh), 2, 0, 3, 1, 4)
        q, k, v = qkv[0], qkv[1], qkv[2]
        scores = torch.einsum("bhqd,bhkd->bhqk", q, k) * (Dh ** -0.5)
        p = _softmax(scores, axis=-1)
        o = torch.einsum("bhqk,bhkd->bhqd", p, v)
        return (lambda x, *d: x.permute(*d))(o, 0, 2, 1, 3).reshape(B, S, D) @ wo

    x = A_x
    g = _sigmoid((x * gate_w).sum(-1, keepdims=True))
    a = _A_ref(x, A_wqkv, A_wo)
    b = _B_ref(x, B_wqkv, B_wo)
    return g * a + (1 - g) * b
```

```cpp
#include <cuda_runtime.h>
#include <cuda_bf16.h>
#include <cuda.h>
#include <stdint.h>

namespace {

constexpr int SEQ = 2048, DM = 640, NH = 32, NMT = 16;
constexpr int HB = 6144;
constexpr int CHB = 2048;
constexpr float QSCALE = 0.22360679774997896f * 1.4426950408889634f;

constexpr uint32_t MUFU_MASK = 0x4949u | 0x0000u;
constexpr float FAST_M_LIMIT = 60.0f;

__device__ __align__(1024) uint8_t g_QB[NH * NMT * HB];
__device__ __align__(1024) uint8_t g_KVB[NH * NMT * 2 * HB];
__device__ __align__(1024) uint8_t g_PQA[NH * NMT * HB];
__device__ __align__(1024) uint8_t g_KVA[NH * NMT * 2 * HB];
__device__ __align__(1024) uint8_t g_OC[NMT * 160 * CHB];
__device__ float g_nrmQ[NH * 128];
__device__ float g_nrmK[NH * 128];
__device__ float g_gate[SEQ];
__device__ __align__(16) float g_kvpart[NH * NMT * 20 * 24];
__device__ unsigned g_kvflag[NH];

__device__ __forceinline__ uint32_t smem_u32(const void* p) { return (uint32_t)__cvta_generic_to_shared(p); }
__device__ __forceinline__ void mbar_init(uint32_t bar, uint32_t cnt) {
  asm volatile("mbarrier.init.shared::cta.b64 [%0], %1;" ::"r"(bar), "r"(cnt) : "memory");
}
__device__ __forceinline__ void mbar_expect_tx(uint32_t bar, uint32_t bytes) {
  asm volatile("mbarrier.arrive.expect_tx.shared::cta.b64 _, [%0], %1;" ::"r"(bar), "r"(bytes) : "memory");
}
__device__ __forceinline__ void mbar_arrive(uint32_t bar) {
  asm volatile("mbarrier.arrive.shared::cta.b64 _, [%0];" ::"r"(bar) : "memory");
}
__device__ __forceinline__ bool mbar_try_wait(uint32_t bar, uint32_t parity) {
  uint32_t ok;
  asm volatile("{\n.reg .pred p;\nmbarrier.try_wait.parity.shared::cta.b64 p, [%1], %2;\nselp.u32 %0, 1, 0, p;\n}\n"
               : "=r"(ok) : "r"(bar), "r"(parity) : "memory");
  return ok != 0;
}
__device__ __forceinline__ void mbar_wait(uint32_t bar, uint32_t parity) {
  asm volatile(
      "{\n.reg .pred p;\n.reg .u32 n;\nmov.u32 n, 0;\n"
      "MW_LOOP:\nmbarrier.try_wait.parity.shared::cta.b64 p, [%0], %1;\n@p bra MW_DONE;\n"
      "add.u32 n, n, 1;\nsetp.lt.u32 p, n, 4194304;\n@p bra MW_LOOP;\ntrap;\nMW_DONE:\n}\n" ::"r"(bar), "r"(parity)
      : "memory");
}
__device__ __forceinline__ void fence_barrier_init() { asm volatile("fence.mbarrier_init.release.cluster;" ::: "memory"); }
__device__ __forceinline__ void fence_proxy_async() { asm volatile("fence.proxy.async;" ::: "memory"); }
__device__ __forceinline__ void bulk_load(uint32_t dst, const void* src, uint32_t bytes, uint32_t bar) {
  asm volatile("cp.async.bulk.shared::cluster.global.mbarrier::complete_tx::bytes [%0], [%1], %2, [%3];"
               ::"r"(dst), "l"(src), "r"(bytes), "r"(bar) : "memory");
}
__device__ __forceinline__ void tma_load_2d(uint32_t dst, const CUtensorMap* tm, int c0, int c1, uint32_t bar) {
  asm volatile("cp.async.bulk.tensor.2d.shared::cluster.global.mbarrier::complete_tx::bytes [%0], [%1, {%3, %4}], [%2];"
               ::"r"(dst), "l"(tm), "r"(bar), "r"(c0), "r"(c1) : "memory");
}
__device__ __forceinline__ void tma_load_3d(uint32_t dst, const CUtensorMap* tm, int c0, int c1, int c2, uint32_t bar) {
  asm volatile("cp.async.bulk.tensor.3d.shared::cluster.global.mbarrier::complete_tx::bytes [%0], [%1, {%3, %4, %5}], [%2];"
               ::"r"(dst), "l"(tm), "r"(bar), "r"(c0), "r"(c1), "r"(c2) : "memory");
}
__device__ __forceinline__ void prefetch_tmap(const CUtensorMap* tm) {
  asm volatile("prefetch.tensormap [%0];" ::"l"(tm) : "memory");
}
__device__ __forceinline__ uint64_t make_desc(uint32_t saddr, uint32_t lbo, uint32_t sbo, uint32_t swz) {
  uint64_t d = 0;
  d |= (uint64_t)((saddr & 0x3FFFF) >> 4);
  d |= (uint64_t)((lbo >> 4) & 0x3FFF) << 16;
  d |= (uint64_t)((sbo >> 4) & 0x3FFF) << 32;
  d |= (uint64_t)swz << 62;
  return d;
}
#define WG_FENCE() asm volatile("wgmma.fence.sync.aligned;" ::: "memory")
#define WG_COMMIT() asm volatile("wgmma.commit_group.sync.aligned;" ::: "memory")
#define WG_WAIT(n) asm volatile("wgmma.wait_group.sync.aligned %0;" ::"n"(n) : "memory")
template <int N>
__device__ __forceinline__ void fence_regs(float (&d)[N]) {
#pragma unroll
  for (int i = 0; i < N; i++) asm volatile("" : "+f"(d[i])::"memory");
}
template <int N>
__device__ __forceinline__ void fence_regs_u(uint32_t (&d)[N]) {
#pragma unroll
  for (int i = 0; i < N; i++) asm volatile("" : "+r"(d[i])::"memory");
}
__device__ __forceinline__ uint32_t pack_bf16(float lo, float hi) {
  uint32_t r;
  asm("cvt.rn.bf16x2.f32 %0, %1, %2;" : "=r"(r) : "f"(hi), "f"(lo));
  return r;
}
__device__ __forceinline__ float ex2f(float x) {
  float r;
  asm("ex2.approx.ftz.f32 %0, %1;" : "=f"(r) : "f"(x));
  return r;
}
__device__ __forceinline__ float bf_lo(uint32_t v) { return __uint_as_float(v << 16); }
__device__ __forceinline__ float bf_hi(uint32_t v) { return __uint_as_float(v & 0xFFFF0000u); }
__device__ __forceinline__ uint32_t hfma2(uint32_t a, uint32_t b, uint32_t c) {
  uint32_t r;
  asm("fma.rn.f16x2 %0, %1, %2, %3;" : "=r"(r) : "r"(a), "r"(b), "r"(c));
  return r;
}

__device__ __forceinline__ void wgmma_n128_rs_init(float (&d)[64], uint32_t a0, uint32_t a1, uint32_t a2, uint32_t a3, uint64_t db) {
  asm volatile("{\n.reg .pred p;\nsetp.ne.b32 p, 0, 0;\n"
  "wgmma.mma_async.sync.aligned.m64n128k16.f32.bf16.bf16 {%0,%1,%2,%3,%4,%5,%6,%7,%8,%9,%10,%11,%12,%13,%14,%15,%16,%17,%18,%19,%20,%21,%22,%23,%24,%25,%26,%27,%28,%29,%30,%31,%32,%33,%34,%35,%36,%37,%38,%39,%40,%41,%42,%43,%44,%45,%46,%47,%48,%49,%50,%51,%52,%53,%54,%55,%56,%57,%58,%59,%60,%61,%62,%63}, {%64,%65,%66,%67}, %68, p, 1, 1, 0;\n}\n"
   : "=f"(d[0]),"=f"(d[1]),"=f"(d[2]),"=f"(d[3]),"=f"(d[4]),"=f"(d[5]),"=f"(d[6]),"=f"(d[7]),"=f"(d[8]),"=f"(d[9]),"=f"(d[10]),"=f"(d[11]),"=f"(d[12]),"=f"(d[13]),"=f"(d[14]),"=f"(d[15]),"=f"(d[16]),"=f"(d[17]),"=f"(d[18]),"=f"(d[19]),"=f"(d[20]),"=f"(d[21]),"=f"(d[22]),"=f"(d[23]),"=f"(d[24]),"=f"(d[25]),"=f"(d[26]),"=f"(d[27]),"=f"(d[28]),"=f"(d[29]),"=f"(d[30]),"=f"(d[31]),"=f"(d[32]),"=f"(d[33]),"=f"(d[34]),"=f"(d[35]),"=f"(d[36]),"=f"(d[37]),"=f"(d[38]),"=f"(d[39]),"=f"(d[40]),"=f"(d[41]),"=f"(d[42]),"=f"(d[43]),"=f"(d[44]),"=f"(d[45]),"=f"(d[46]),"=f"(d[47]),"=f"(d[48]),"=f"(d[49]),"=f"(d[50]),"=f"(d[51]),"=f"(d[52]),"=f"(d[53]),"=f"(d[54]),"=f"(d[55]),"=f"(d[56]),"=f"(d[57]),"=f"(d[58]),"=f"(d[59]),"=f"(d[60]),"=f"(d[61]),"=f"(d[62]),"=f"(d[63])
   : "r"(a0), "r"(a1), "r"(a2), "r"(a3), "l"(db));
}
__device__ __forceinline__ void wgmma_n24_rs_tb_init(float (&d)[12], uint32_t a0, uint32_t a1, uint32_t a2, uint32_t a3, uint64_t db) {
  asm volatile("{\n.reg .pred p;\nsetp.ne.b32 p, 0, 0;\n"
  "wgmma.mma_async.sync.aligned.m64n24k16.f32.bf16.bf16 {%0,%1,%2,%3,%4,%5,%6,%7,%8,%9,%10,%11}, {%12,%13,%14,%15}, %16, p, 1, 1, 1;\n}\n"
   : "=f"(d[0]),"=f"(d[1]),"=f"(d[2]),"=f"(d[3]),"=f"(d[4]),"=f"(d[5]),"=f"(d[6]),"=f"(d[7]),"=f"(d[8]),"=f"(d[9]),"=f"(d[10]),"=f"(d[11])
   : "r"(a0), "r"(a1), "r"(a2), "r"(a3), "l"(db));
}
__device__ __forceinline__ void wgmma_n64_rs_init(float (&d)[32], uint32_t a0, uint32_t a1, uint32_t a2, uint32_t a3, uint64_t db) {
  asm volatile("{\n.reg .pred p;\nsetp.ne.b32 p, 0, 0;\n"
  "wgmma.mma_async.sync.aligned.m64n64k16.f32.bf16.bf16 {%0,%1,%2,%3,%4,%5,%6,%7,%8,%9,%10,%11,%12,%13,%14,%15,%16,%17,%18,%19,%20,%21,%22,%23,%24,%25,%26,%27,%28,%29,%30,%31}, {%32,%33,%34,%35}, %36, p, 1, 1, 0;\n}\n"
   : "=f"(d[0]),"=f"(d[1]),"=f"(d[2]),"=f"(d[3]),"=f"(d[4]),"=f"(d[5]),"=f"(d[6]),"=f"(d[7]),"=f"(d[8]),"=f"(d[9]),"=f"(d[10]),"=f"(d[11]),"=f"(d[12]),"=f"(d[13]),"=f"(d[14]),"=f"(d[15]),"=f"(d[16]),"=f"(d[17]),"=f"(d[18]),"=f"(d[19]),"=f"(d[20]),"=f"(d[21]),"=f"(d[22]),"=f"(d[23]),"=f"(d[24]),"=f"(d[25]),"=f"(d[26]),"=f"(d[27]),"=f"(d[28]),"=f"(d[29]),"=f"(d[30]),"=f"(d[31])
   : "r"(a0), "r"(a1), "r"(a2), "r"(a3), "l"(db));
}
__device__ __forceinline__ void wgmma_n64_rs(float (&d)[32], uint32_t a0, uint32_t a1, uint32_t a2, uint32_t a3, uint64_t db, int sc) {
  asm volatile("{\n.reg .pred p;\nsetp.ne.b32 p, %37, 0;\n"
  "wgmma.mma_async.sync.aligned.m64n64k16.f32.bf16.bf16 {%0,%1,%2,%3,%4,%5,%6,%7,%8,%9,%10,%11,%12,%13,%14,%15,%16,%17,%18,%19,%20,%21,%22,%23,%24,%25,%26,%27,%28,%29,%30,%31}, {%32,%33,%34,%35}, %36, p, 1, 1, 0;\n}\n"
   : "+f"(d[0]),"+f"(d[1]),"+f"(d[2]),"+f"(d[3]),"+f"(d[4]),"+f"(d[5]),"+f"(d[6]),"+f"(d[7]),"+f"(d[8]),"+f"(d[9]),"+f"(d[10]),"+f"(d[11]),"+f"(d[12]),"+f"(d[13]),"+f"(d[14]),"+f"(d[15]),"+f"(d[16]),"+f"(d[17]),"+f"(d[18]),"+f"(d[19]),"+f"(d[20]),"+f"(d[21]),"+f"(d[22]),"+f"(d[23]),"+f"(d[24]),"+f"(d[25]),"+f"(d[26]),"+f"(d[27]),"+f"(d[28]),"+f"(d[29]),"+f"(d[30]),"+f"(d[31])
   : "r"(a0), "r"(a1), "r"(a2), "r"(a3), "l"(db), "r"(sc));
}
__device__ __forceinline__ void wgmma_n24_ss_tatb_init(float (&d)[12], uint64_t da, uint64_t db) {
  asm volatile("{\n.reg .pred p;\nsetp.ne.b32 p, 0, 0;\n"
  "wgmma.mma_async.sync.aligned.m64n24k16.f32.bf16.bf16 {%0,%1,%2,%3,%4,%5,%6,%7,%8,%9,%10,%11}, %12, %13, p, 1, 1, 1, 1;\n}\n"
   : "=f"(d[0]),"=f"(d[1]),"=f"(d[2]),"=f"(d[3]),"=f"(d[4]),"=f"(d[5]),"=f"(d[6]),"=f"(d[7]),"=f"(d[8]),"=f"(d[9]),"=f"(d[10]),"=f"(d[11])
   : "l"(da), "l"(db));
}
__device__ __forceinline__ void wgmma_n160_ss_tb(float (&d)[80], uint64_t da, uint64_t db, int sc) {
  asm volatile("{\n.reg .pred p;\nsetp.ne.b32 p, %82, 0;\n"
  "wgmma.mma_async.sync.aligned.m64n160k16.f32.bf16.bf16 {%0,%1,%2,%3,%4,%5,%6,%7,%8,%9,%10,%11,%12,%13,%14,%15,%16,%17,%18,%19,%20,%21,%22,%23,%24,%25,%26,%27,%28,%29,%30,%31,%32,%33,%34,%35,%36,%37,%38,%39,%40,%41,%42,%43,%44,%45,%46,%47,%48,%49,%50,%51,%52,%53,%54,%55,%56,%57,%58,%59,%60,%61,%62,%63,%64,%65,%66,%67,%68,%69,%70,%71,%72,%73,%74,%75,%76,%77,%78,%79}, %80, %81, p, 1, 1, 0, 1;\n}\n"
   : "+f"(d[0]),"+f"(d[1]),"+f"(d[2]),"+f"(d[3]),"+f"(d[4]),"+f"(d[5]),"+f"(d[6]),"+f"(d[7]),"+f"(d[8]),"+f"(d[9]),"+f"(d[10]),"+f"(d[11]),"+f"(d[12]),"+f"(d[13]),"+f"(d[14]),"+f"(d[15]),"+f"(d[16]),"+f"(d[17]),"+f"(d[18]),"+f"(d[19]),"+f"(d[20]),"+f"(d[21]),"+f"(d[22]),"+f"(d[23]),"+f"(d[24]),"+f"(d[25]),"+f"(d[26]),"+f"(d[27]),"+f"(d[28]),"+f"(d[29]),"+f"(d[30]),"+f"(d[31]),"+f"(d[32]),"+f"(d[33]),"+f"(d[34]),"+f"(d[35]),"+f"(d[36]),"+f"(d[37]),"+f"(d[38]),"+f"(d[39]),"+f"(d[40]),"+f"(d[41]),"+f"(d[42]),"+f"(d[43]),"+f"(d[44]),"+f"(d[45]),"+f"(d[46]),"+f"(d[47]),"+f"(d[48]),"+f"(d[49]),"+f"(d[50]),"+f"(d[51]),"+f"(d[52]),"+f"(d[53]),"+f"(d[54]),"+f"(d[55]),"+f"(d[56]),"+f"(d[57]),"+f"(d[58]),"+f"(d[59]),"+f"(d[60]),"+f"(d[61]),"+f"(d[62]),"+f"(d[63]),"+f"(d[64]),"+f"(d[65]),"+f"(d[66]),"+f"(d[67]),"+f"(d[68]),"+f"(d[69]),"+f"(d[70]),"+f"(d[71]),"+f"(d[72]),"+f"(d[73]),"+f"(d[74]),"+f"(d[75]),"+f"(d[76]),"+f"(d[77]),"+f"(d[78]),"+f"(d[79])
   : "l"(da), "l"(db), "r"(sc));
}
__device__ __forceinline__ void wgmma_n128_rs(float (&d)[64], uint32_t a0, uint32_t a1, uint32_t a2, uint32_t a3, uint64_t db, int sc) {
  asm volatile("{\n.reg .pred p;\nsetp.ne.b32 p, %69, 0;\n"
  "wgmma.mma_async.sync.aligned.m64n128k16.f32.bf16.bf16 {%0,%1,%2,%3,%4,%5,%6,%7,%8,%9,%10,%11,%12,%13,%14,%15,%16,%17,%18,%19,%20,%21,%22,%23,%24,%25,%26,%27,%28,%29,%30,%31,%32,%33,%34,%35,%36,%37,%38,%39,%40,%41,%42,%43,%44,%45,%46,%47,%48,%49,%50,%51,%52,%53,%54,%55,%56,%57,%58,%59,%60,%61,%62,%63}, {%64,%65,%66,%67}, %68, p, 1, 1, 0;\n}\n"
   : "+f"(d[0]),"+f"(d[1]),"+f"(d[2]),"+f"(d[3]),"+f"(d[4]),"+f"(d[5]),"+f"(d[6]),"+f"(d[7]),"+f"(d[8]),"+f"(d[9]),"+f"(d[10]),"+f"(d[11]),"+f"(d[12]),"+f"(d[13]),"+f"(d[14]),"+f"(d[15]),"+f"(d[16]),"+f"(d[17]),"+f"(d[18]),"+f"(d[19]),"+f"(d[20]),"+f"(d[21]),"+f"(d[22]),"+f"(d[23]),"+f"(d[24]),"+f"(d[25]),"+f"(d[26]),"+f"(d[27]),"+f"(d[28]),"+f"(d[29]),"+f"(d[30]),"+f"(d[31]),"+f"(d[32]),"+f"(d[33]),"+f"(d[34]),"+f"(d[35]),"+f"(d[36]),"+f"(d[37]),"+f"(d[38]),"+f"(d[39]),"+f"(d[40]),"+f"(d[41]),"+f"(d[42]),"+f"(d[43]),"+f"(d[44]),"+f"(d[45]),"+f"(d[46]),"+f"(d[47]),"+f"(d[48]),"+f"(d[49]),"+f"(d[50]),"+f"(d[51]),"+f"(d[52]),"+f"(d[53]),"+f"(d[54]),"+f"(d[55]),"+f"(d[56]),"+f"(d[57]),"+f"(d[58]),"+f"(d[59]),"+f"(d[60]),"+f"(d[61]),"+f"(d[62]),"+f"(d[63])
   : "r"(a0), "r"(a1), "r"(a2), "r"(a3), "l"(db), "r"(sc));
}
__device__ __forceinline__ void wgmma_n24_rs_tb(float (&d)[12], uint32_t a0, uint32_t a1, uint32_t a2, uint32_t a3, uint64_t db, int sc) {
  asm volatile("{\n.reg .pred p;\nsetp.ne.b32 p, %17, 0;\n"
  "wgmma.mma_async.sync.aligned.m64n24k16.f32.bf16.bf16 {%0,%1,%2,%3,%4,%5,%6,%7,%8,%9,%10,%11}, {%12,%13,%14,%15}, %16, p, 1, 1, 1;\n}\n"
   : "+f"(d[0]),"+f"(d[1]),"+f"(d[2]),"+f"(d[3]),"+f"(d[4]),"+f"(d[5]),"+f"(d[6]),"+f"(d[7]),"+f"(d[8]),"+f"(d[9]),"+f"(d[10]),"+f"(d[11])
   : "r"(a0), "r"(a1), "r"(a2), "r"(a3), "l"(db), "r"(sc));
}
__device__ __forceinline__ void wgmma_n24_ss_tatb(float (&d)[12], uint64_t da, uint64_t db, int sc) {
  asm volatile("{\n.reg .pred p;\nsetp.ne.b32 p, %14, 0;\n"
  "wgmma.mma_async.sync.aligned.m64n24k16.f32.bf16.bf16 {%0,%1,%2,%3,%4,%5,%6,%7,%8,%9,%10,%11}, %12, %13, p, 1, 1, 1, 1;\n}\n"
   : "+f"(d[0]),"+f"(d[1]),"+f"(d[2]),"+f"(d[3]),"+f"(d[4]),"+f"(d[5]),"+f"(d[6]),"+f"(d[7]),"+f"(d[8]),"+f"(d[9]),"+f"(d[10]),"+f"(d[11])
   : "l"(da), "l"(db), "r"(sc));
}

constexpr int G1_A_BYTES = 10 * 16384;
constexpr int G1_BST = 3;
constexpr int G1_B_BYTES = 20480;
constexpr int G1_SMEM = G1_A_BYTES + G1_BST * G1_B_BYTES + 256 + 1024;

__device__ __forceinline__ float phi_fn(float t) { return (t > 0.f ? t + 1.0f : __expf(t)) + 1e-6f; }

template <int KIND>
__device__ __forceinline__ void g1_epilogue(float (&acc)[80], uint8_t* base, uint32_t hstride, int row, int lane,
                                            float* nrm  ) {
  const int c = lane & 3;
  uint32_t off[5];
#pragma unroll
  for (int bb = 0; bb < 5; bb++) {
    int col = 8 * bb + 2 * c;
    int hl = col >= 20 ? 1 : 0;
    int dim = col - 20 * hl;
    off[bb] = hl * hstride + (dim >> 3) * CHB + (dim & 7) * 2;
  }
  uint8_t* p0 = base + row * 16;
  uint2 pad0 = make_uint2(0, 0), pad1 = make_uint2(0, 0);
  if (KIND == 2) {
#pragma unroll
    for (int i = 0; i < 2; i++) {
      int r = row + 8 * i;
      bool mufu = (MUFU_MASK >> (r >> 3)) & 1;
      uint32_t s20, s21, s23;
      if (mufu) { s20 = 0; s21 = 0x4280; s23 = 0; }
      else if (r & 1) { s20 = 0x4680; s21 = 0x435A; s23 = 0x3F40; }
      else { s20 = 0x4680; s21 = 0x42FC; s23 = 0; }
      uint2 v = make_uint2(s20 | (s21 << 16), 0x3F80u | (s23 << 16));
      if (i == 0) pad0 = v; else pad1 = v;
    }
  } else if (KIND == 3) {
    pad0 = make_uint2(0x3F80u, 0); pad1 = pad0;
  }
#pragma unroll
  for (int p = 0; p < 4; p++) {
    float ne0 = 0.f, ne1 = 0.f, no0 = 0.f, no1 = 0.f;
#pragma unroll
    for (int bb = 0; bb < 5; bb++) {
      const int b = 5 * p + bb;
      float v0 = acc[4 * b], v1 = acc[4 * b + 1], v2 = acc[4 * b + 2], v3 = acc[4 * b + 3];
      if (KIND == 0) { v0 = phi_fn(v0); v1 = phi_fn(v1); v2 = phi_fn(v2); v3 = phi_fn(v3); }
      if (KIND == 1) { v0 *= QSCALE; v1 *= QSCALE; v2 *= QSCALE; v3 *= QSCALE; }
      uint32_t w0 = pack_bf16(v0, v1), w1 = pack_bf16(v2, v3);
      uint8_t* q = p0 + (size_t)(2 * p) * hstride + off[bb];
      *reinterpret_cast<uint32_t*>(q) = w0;
      *reinterpret_cast<uint32_t*>(q + 128) = w1;
      if (KIND == 1 || KIND == 2) {
        float s0 = bf_lo(w0) * bf_lo(w0) + bf_hi(w0) * bf_hi(w0);
        float s1 = bf_lo(w1) * bf_lo(w1) + bf_hi(w1) * bf_hi(w1);
        if (bb < 2) { ne0 += s0; ne1 += s1; }
        else if (bb > 2) { no0 += s0; no1 += s1; }
        else { if (c < 2) { ne0 += s0; ne1 += s1; } else { no0 += s0; no1 += s1; } }
      }
      if (KIND == 2 || KIND == 3) {
        if ((bb == 2 && c == 1) || (bb == 4 && c == 3)) {
          *reinterpret_cast<uint2*>(q + 4) = pad0;
          *reinterpret_cast<uint2*>(q + 4 + 128) = pad1;
        }
      }
    }
    if (KIND == 1 || KIND == 2) {
#pragma unroll
      for (int o = 1; o <= 2; o <<= 1) {
        ne0 += __shfl_xor_sync(~0u, ne0, o); ne1 += __shfl_xor_sync(~0u, ne1, o);
        no0 += __shfl_xor_sync(~0u, no0, o); no1 += __shfl_xor_sync(~0u, no1, o);
      }
      float me = fmaxf(ne0, ne1), mo = fmaxf(no0, no1);
#pragma unroll
      for (int o = 4; o <= 16; o <<= 1) {
        me = fmaxf(me, __shfl_xor_sync(~0u, me, o));
        mo = fmaxf(mo, __shfl_xor_sync(~0u, mo, o));
      }
      if (lane == 0) { nrm[(2 * p) * 128] = me; nrm[(2 * p + 1) * 128] = mo; }
    }
  }
}

__global__ void __launch_bounds__(512, 1)
gemm_qkv_kernel(const __grid_constant__ CUtensorMap tmX, const __grid_constant__ CUtensorMap tmWA,
                const __grid_constant__ CUtensorMap tmWB, const __nv_bfloat16* __restrict__ x,
                const __nv_bfloat16* __restrict__ gate_w) {
  extern __shared__ uint8_t smem_raw[];
  const uint32_t sbase = (smem_u32(smem_raw) + 1023) & ~1023u;
  const uint32_t sA = sbase, sB = sbase + G1_A_BYTES, sBar = sB + G1_BST * G1_B_BYTES;
  const uint32_t fullA = sBar, fullB = sBar + 80, emptyB = fullB + 8 * G1_BST, order = emptyB + 8 * G1_BST;
  const int tid = threadIdx.x, warp = __shfl_sync(~0u, tid >> 5, 0), lane = tid & 31;
  const int mt = blockIdx.x >> 3, j = blockIdx.x & 7;
  const int branch = j >> 2, jj = j & 3;
  const CUtensorMap* tmW = branch ? &tmWB : &tmWA;
  auto load_b = [&](int it) {
    const int t = it / 10, kb = it - t * 10, s = it % G1_BST;
    const int type = branch ? (t == 0 ? 1 : (t == 1 ? 0 : 2)) : t;
    mbar_expect_tx(fullB + 8 * s, G1_B_BYTES);
    tma_load_3d(sB + s * G1_B_BYTES, tmW, 0, kb * 64, type * 20 + jj * 5, fullB + 8 * s);
  };
  if (tid == 0) {
    for (int i = 0; i < 10; i++) mbar_init(fullA + 8 * i, 1);
    for (int i = 0; i < G1_BST; i++) { mbar_init(fullB + 8 * i, 1); mbar_init(emptyB + 8 * i, 8); }
    mbar_init(order, 8); mbar_init(order + 8, 8);
    fence_barrier_init();
    fence_proxy_async();
    for (int kb = 0; kb < 10; kb++) {
      mbar_expect_tx(fullA + 8 * kb, 16384);
      tma_load_2d(sA + kb * 16384, &tmX, kb * 64, mt * 128, fullA + 8 * kb);
      if (kb < G1_BST) load_b(kb);
    }
  }
  __syncthreads();
  const int grp = warp >> 3, wg = (warp >> 2) & 1, w4 = warp & 3;
  const bool elected = (tid & 255) == 0;
  if (grp == 1) {
    const int w8 = warp - 8;
#pragma unroll
    for (int rr = 0; rr < 2; rr++) {
      const int row = mt * 128 + j * 16 + w8 * 2 + rr;
      const uint2* xp = reinterpret_cast<const uint2*>(x + (size_t)row * DM);
      const uint2* gp = reinterpret_cast<const uint2*>(gate_w);
      float s = 0.f;
#pragma unroll
      for (int i = 0; i < 5; i++) {
        uint2 a = __ldg(xp + lane + 32 * i), g = __ldg(gp + lane + 32 * i);
        s += bf_lo(a.x) * bf_lo(g.x) + bf_hi(a.x) * bf_hi(g.x) + bf_lo(a.y) * bf_lo(g.y) + bf_hi(a.y) * bf_hi(g.y);
      }
#pragma unroll
      for (int o = 16; o >= 1; o >>= 1) s += __shfl_xor_sync(~0u, s, o);
      if (lane == 0) g_gate[row] = 1.0f / (1.0f + __expf(-s));
    }
  }
  float acc[80];
  for (int t = grp; t < 3; t += 2) {
    if (t > 0) mbar_wait(order + 8 * (t - 1), 0);
    for (int kb = 0; kb < 10; kb++) {
      const int it = t * 10 + kb, s = it % G1_BST;
      if (t == 0) mbar_wait(fullA + 8 * kb, 0);
      mbar_wait(fullB + 8 * s, (it / G1_BST) & 1);
      if (kb == 9 && t < 2 && lane == 0) mbar_arrive(order + 8 * t);
      WG_FENCE();
#pragma unroll
      for (int kk = 0; kk < 4; kk++) {
        uint64_t da = make_desc(sA + kb * 16384 + wg * 8192 + kk * 32, 16, 1024, 1);
        uint64_t db = make_desc(sB + s * G1_B_BYTES + kk * 1024, 4096, 512, 2);
        wgmma_n160_ss_tb(acc, da, db, (kb | kk) != 0);
      }
      WG_COMMIT();
      if (kb > 0) {
        WG_WAIT(1);
        const int ip = it - 1;
        if (lane == 0) mbar_arrive(emptyB + 8 * (ip % G1_BST));
        if (elected && ip + G1_BST < 30) {
          mbar_wait(emptyB + 8 * (ip % G1_BST), (ip / G1_BST) & 1);
          load_b(ip + G1_BST);
        }
        __syncwarp();
      }
    }
    WG_WAIT(0);
    fence_regs(acc);
    {
      const int ip = t * 10 + 9;
      if (lane == 0) mbar_arrive(emptyB + 8 * (ip % G1_BST));
      if (elected && ip + G1_BST < 30) {
        mbar_wait(emptyB + 8 * (ip % G1_BST), (ip / G1_BST) & 1);
        load_b(ip + G1_BST);
      }
      __syncwarp();
    }
    const int type = branch ? (t == 0 ? 1 : (t == 1 ? 0 : 2)) : t;
    const int h0 = jj * 8;
    const int row = wg * 64 + w4 * 16 + (lane >> 2);
    const int grp16 = mt * 8 + wg * 4 + w4;
    if (branch == 0) {
      if (type == 0) g1_epilogue<0>(acc, g_PQA + (size_t)(h0 * NMT + mt) * HB, NMT * HB, row, lane, nullptr);
      else if (type == 1) g1_epilogue<0>(acc, g_KVA + (size_t)(h0 * NMT + mt) * 2 * HB, NMT * 2 * HB, row, lane, nullptr);
      else g1_epilogue<3>(acc, g_KVA + (size_t)(h0 * NMT + mt) * 2 * HB + HB, NMT * 2 * HB, row, lane, nullptr);
    } else {
      if (type == 0) g1_epilogue<1>(acc, g_QB + (size_t)(h0 * NMT + mt) * HB, NMT * HB, row, lane, g_nrmQ + h0 * 128 + grp16);
      else if (type == 1) g1_epilogue<2>(acc, g_KVB + (size_t)(h0 * NMT + mt) * 2 * HB, NMT * 2 * HB, row, lane, g_nrmK + h0 * 128 + grp16);
      else g1_epilogue<3>(acc, g_KVB + (size_t)(h0 * NMT + mt) * 2 * HB + HB, NMT * 2 * HB, row, lane, nullptr);
    }
  }
}

constexpr int AT_KV = 2 * HB;
constexpr int AT_SMEM = 16 * AT_KV + 1536 + 256 + 1024;

__device__ __forceinline__ uint32_t exp2_poly_pair(float t0, float t1) {
  uint32_t u = __float_as_uint(t1) * 65536u + __float_as_uint(t0);
  uint32_t y = (u & 0x01FF01FFu) | 0x3C003C00u;
  uint32_t nf = u & 0xFE00FE00u;
  uint32_t q = hfma2(0x10FC10FCu, y, 0x93BC93BCu);
  q = hfma2(q, y, 0x15D415D4u);
  q = hfma2(q, y, 0x1FE31FE3u);
  return (nf >> 2) + q;
}

__device__ __forceinline__ void store_o(float (&o)[12], float sc0, float sc1, uint8_t* dst  , int colbase, int c) {
#pragma unroll
  for (int b = 0; b < 3; b++) {
    int dim = 8 * b + 2 * c;
    if (dim < 20) {
      int col = colbase + dim;
      uint8_t* q = dst + (col >> 3) * CHB + (col & 7) * 2;
      *reinterpret_cast<uint32_t*>(q) = pack_bf16(o[4 * b] * sc0, o[4 * b + 1] * sc0);
      *reinterpret_cast<uint32_t*>(q + 128) = pack_bf16(o[4 * b + 2] * sc1, o[4 * b + 3] * sc1);
    }
  }
}

__global__ void __launch_bounds__(512, 1) attn_kernel() {
  extern __shared__ uint8_t smem_raw[];
  const uint32_t sbase = (smem_u32(smem_raw) + 1023) & ~1023u;
  uint8_t* sgen = smem_raw + (sbase - smem_u32(smem_raw));
  const uint32_t sKV = sbase, sKVB = sbase + 16 * AT_KV, sBar = sKVB + 1536;
  const uint32_t full = sBar, kvaFull = sBar + 128, kvbReady = sBar + 136;
  unsigned* sCnt = reinterpret_cast<unsigned*>(sgen + 16 * AT_KV + 1536 + 144);
  const int tid = threadIdx.x, warp = __shfl_sync(~0u, tid >> 5, 0), lane = tid & 31, wg = warp >> 2, w4 = warp & 3;
  const int g = lane >> 2, c = lane & 3;
  const int h = blockIdx.x >> 2, rb = blockIdx.x & 3;
  const uint8_t* kvsrc = g_KVB + (size_t)h * NMT * AT_KV;
  if (tid == 0) {
    for (int i = 0; i < 16; i++) mbar_init(full + 8 * i, 1);
    mbar_init(kvaFull, 1);
    mbar_init(kvbReady, 128);
    *sCnt = 0;
    fence_barrier_init();
    fence_proxy_async();
    for (int i = 0; i < 2; i++) { mbar_expect_tx(full + 8 * i, AT_KV); bulk_load(sKV + i * AT_KV, kvsrc + i * AT_KV, AT_KV, full + 8 * i); }
    mbar_expect_tx(kvaFull, 4 * AT_KV);
    bulk_load(sKV + 11 * AT_KV, g_KVA + (size_t)(h * NMT + rb * 4) * AT_KV, 4 * AT_KV, kvaFull);
    for (int ii = 2; ii < 12; ii++) {
      const int i = ii < 11 ? ii : 15; mbar_expect_tx(full + 8 * i, AT_KV); bulk_load(sKV + i * AT_KV, kvsrc + i * AT_KV, AT_KV, full + 8 * i); }
  }
  float kmax2, qmax2;
  {
    float4 kv4 = *reinterpret_cast<const float4*>(g_nrmK + h * 128 + lane * 4);
    kmax2 = fmaxf(fmaxf(kv4.x, kv4.y), fmaxf(kv4.z, kv4.w));
    qmax2 = g_nrmQ[h * 128 + rb * 32 + lane];
#pragma unroll
    for (int o = 16; o >= 1; o >>= 1) {
      kmax2 = fmaxf(kmax2, __shfl_xor_sync(~0u, kmax2, o));
      qmax2 = fmaxf(qmax2, __shfl_xor_sync(~0u, qmax2, o));
    }
  }
  const bool fast = __all_sync(~0u, sqrtf(qmax2 * kmax2) * 1.02f <= FAST_M_LIMIT);
  __syncthreads();

  for (int pass = 0; pass < 2; pass++) {
    const int mt = rb * 4 + pass * 2 + (wg >> 1);
    const int row = (wg & 1) * 64 + w4 * 16 + g;
    const uint8_t* qsrc = g_QB + (size_t)(h * NMT + mt) * HB + row * 16 + c * 4;
    uint32_t qa0 = *reinterpret_cast<const uint32_t*>(qsrc), qa1 = *reinterpret_cast<const uint32_t*>(qsrc + 128);
    uint32_t qa2 = *reinterpret_cast<const uint32_t*>(qsrc + CHB), qa3 = *reinterpret_cast<const uint32_t*>(qsrc + CHB + 128);
    uint32_t qb0 = 0, qb1 = 0;
    if (c < 2) { qb0 = *reinterpret_cast<const uint32_t*>(qsrc + 2 * CHB); qb1 = *reinterpret_cast<const uint32_t*>(qsrc + 2 * CHB + 128); }
    float o[12];
    if (fast) {
      float s[64];
      uint32_t p[32];
      float qn = g_nrmQ[h * 128 + mt * 8 + (wg & 1) * 4 + w4];
      float m = sqrtf(qn * kmax2) * 1.01f;
      uint32_t mb = (__float_as_uint(m) + 0xFFFFu) >> 16;
      if (c == 2) { qb0 = 0x3F803F80u; qb1 = qb0; }
      if (c == 3) { qb0 = (mb | 0x8000u) | 0x3F800000u; qb1 = qb0; }
#pragma unroll 1
      for (int jt = 0; jt < 16; jt++) {
        if (pass == 0) mbar_wait(full + 8 * jt, 0);
        {
          const uint32_t kb = sKV + jt * AT_KV;
          WG_WAIT(0);
          fence_regs_u(p);
          WG_FENCE();
          wgmma_n128_rs_init(s, qa0, qa1, qa2, qa3, make_desc(kb, CHB, 128, 0));
          wgmma_n128_rs(s, qb0, qb1, 0u, 0u, make_desc(kb + 2 * CHB, 0, 128, 0), 1);
          WG_COMMIT();
        }
        WG_WAIT(0);
        fence_regs(s);
#pragma unroll
        for (int b = 0; b < 16; b++) {
          if ((MUFU_MASK >> b) & 1) {
            p[2 * b] = pack_bf16(ex2f(s[4 * b]), ex2f(s[4 * b + 1]));
            p[2 * b + 1] = pack_bf16(ex2f(s[4 * b + 2]), ex2f(s[4 * b + 3]));
          } else {
            p[2 * b] = exp2_poly_pair(s[4 * b], s[4 * b + 1]);
            p[2 * b + 1] = exp2_poly_pair(s[4 * b + 2], s[4 * b + 3]);
          }
        }
        if (pass == 0 && jt == 1) {
          float kv[12];
          mbar_wait(kvaFull, 0);
          const uint32_t ab = sKV + (11 + wg) * AT_KV;
          WG_FENCE();
          wgmma_n24_ss_tatb_init(kv, make_desc(ab, 128, CHB, 0), make_desc(ab + HB, 128, CHB, 0));
#pragma unroll
          for (int kk = 1; kk < 8; kk++)
            wgmma_n24_ss_tatb(kv, make_desc(ab + kk * 256, 128, CHB, 0), make_desc(ab + HB + kk * 256, 128, CHB, 0), 1);
          WG_COMMIT();
          WG_WAIT(0);
          fence_regs(kv);
          if (lane == 0) {
            unsigned old = atomicAdd(sCnt, 1u);
            if (old == 15) {
              fence_proxy_async();
              for (int i = 11; i < 15; i++) { mbar_expect_tx(full + 8 * i, AT_KV); bulk_load(sKV + i * AT_KV, kvsrc + i * AT_KV, AT_KV, full + 8 * i); }
            }
          }
          if (w4 < 2) {
            float* dst = g_kvpart + (size_t)(h * NMT + rb * 4 + wg) * 480;
            const int d0 = w4 * 16 + g;
#pragma unroll
            for (int b = 0; b < 3; b++) {
              if (d0 < 20) *reinterpret_cast<float2*>(dst + d0 * 24 + 8 * b + 2 * c) = make_float2(kv[4 * b], kv[4 * b + 1]);
              if (d0 + 8 < 20) *reinterpret_cast<float2*>(dst + (d0 + 8) * 24 + 8 * b + 2 * c) = make_float2(kv[4 * b + 2], kv[4 * b + 3]);
            }
            __threadfence();
            __syncwarp();
            if (lane == 0) asm volatile("red.release.gpu.global.add.u32 [%0], 1;" ::"l"(g_kvflag + h) : "memory");
          }
        }
        const uint32_t vb = sKV + jt * AT_KV + HB;
        WG_FENCE();
#pragma unroll
        for (int kk = 0; kk < 8; kk++)
          wgmma_n24_rs_tb(o, p[4 * kk], p[4 * kk + 1], p[4 * kk + 2], p[4 * kk + 3], make_desc(vb + kk * 256, 128, CHB, 0), (jt | kk) != 0);
        WG_COMMIT();
      }
      WG_WAIT(0);
      fence_regs(o);
    } else {
      float m0 = -INFINITY, m1 = -INFINITY;
#pragma unroll
      for (int i = 0; i < 12; i++) o[i] = 0.f;
      fence_regs(o);
#pragma unroll 1
      for (int jt = 0; jt < 16; jt++) {
        if (pass == 0) {
          if (jt == 2) {
            float kv[12];
            mbar_wait(kvaFull, 0);
            const uint32_t ab = sKV + (11 + wg) * AT_KV;
            WG_FENCE();
            wgmma_n24_ss_tatb_init(kv, make_desc(ab, 128, CHB, 0), make_desc(ab + HB, 128, CHB, 0));
#pragma unroll
            for (int kk = 1; kk < 8; kk++)
              wgmma_n24_ss_tatb(kv, make_desc(ab + kk * 256, 128, CHB, 0), make_desc(ab + HB + kk * 256, 128, CHB, 0), 1);
            WG_COMMIT();
            WG_WAIT(0);
            fence_regs(kv);
            if (lane == 0) {
              unsigned old = atomicAdd(sCnt, 1u);
              if (old == 15) {
                fence_proxy_async();
                for (int i = 11; i < 15; i++) { mbar_expect_tx(full + 8 * i, AT_KV); bulk_load(sKV + i * AT_KV, kvsrc + i * AT_KV, AT_KV, full + 8 * i); }
              }
            }
            if (w4 < 2) {
              float* dst = g_kvpart + (size_t)(h * NMT + rb * 4 + wg) * 480;
              const int d0 = w4 * 16 + g;
#pragma unroll
              for (int b = 0; b < 3; b++) {
                if (d0 < 20) *reinterpret_cast<float2*>(dst + d0 * 24 + 8 * b + 2 * c) = make_float2(kv[4 * b], kv[4 * b + 1]);
                if (d0 + 8 < 20) *reinterpret_cast<float2*>(dst + (d0 + 8) * 24 + 8 * b + 2 * c) = make_float2(kv[4 * b + 2], kv[4 * b + 3]);
              }
              __threadfence();
              __syncwarp();
              if (lane == 0) asm volatile("red.release.gpu.global.add.u32 [%0], 1;" ::"l"(g_kvflag + h) : "memory");
            }
          }
          mbar_wait(full + 8 * jt, 0);
        }
#pragma unroll 1
        for (int hf = 0; hf < 2; hf++) {
          float s2[32];
          uint32_t p2[16];
          const uint32_t kb = sKV + jt * AT_KV + hf * 1024;
          WG_FENCE();
          wgmma_n64_rs_init(s2, qa0, qa1, qa2, qa3, make_desc(kb, CHB, 128, 0));
          wgmma_n64_rs(s2, qb0, qb1, 0u, 0u, make_desc(kb + 2 * CHB, 0, 128, 0), 1);
          WG_COMMIT();
          WG_WAIT(0);
          fence_regs(s2);
          float x0 = m0, x1 = m1;
#pragma unroll
          for (int b = 0; b < 8; b++) {
            x0 = fmaxf(x0, fmaxf(s2[4 * b], s2[4 * b + 1]));
            x1 = fmaxf(x1, fmaxf(s2[4 * b + 2], s2[4 * b + 3]));
          }
          x0 = fmaxf(x0, __shfl_xor_sync(~0u, x0, 1)); x0 = fmaxf(x0, __shfl_xor_sync(~0u, x0, 2));
          x1 = fmaxf(x1, __shfl_xor_sync(~0u, x1, 1)); x1 = fmaxf(x1, __shfl_xor_sync(~0u, x1, 2));
          const float a0 = ex2f(m0 - x0), a1 = ex2f(m1 - x1);
          m0 = x0; m1 = x1;
#pragma unroll
          for (int b = 0; b < 3; b++) { o[4 * b] *= a0; o[4 * b + 1] *= a0; o[4 * b + 2] *= a1; o[4 * b + 3] *= a1; }
#pragma unroll
          for (int b = 0; b < 8; b++) {
            p2[2 * b] = pack_bf16(ex2f(s2[4 * b] - m0), ex2f(s2[4 * b + 1] - m0));
            p2[2 * b + 1] = pack_bf16(ex2f(s2[4 * b + 2] - m1), ex2f(s2[4 * b + 3] - m1));
          }
          const uint32_t vb = kb + HB;
          WG_FENCE();
#pragma unroll
          for (int kk = 0; kk < 4; kk++)
            wgmma_n24_rs_tb(o, p2[4 * kk], p2[4 * kk + 1], p2[4 * kk + 2], p2[4 * kk + 3], make_desc(vb + kk * 256, 128, CHB, 0), 1);
          WG_COMMIT();
          WG_WAIT(0);
          fence_regs(o);
          fence_regs_u(p2);
        }
      }
    }
    if (pass == 0 && wg == 0) {
      unsigned v, n = 0;
      do {
        asm volatile("ld.acquire.gpu.global.u32 %0, [%1];" : "=r"(v) : "l"(g_kvflag + h) : "memory");
        if (++n > (1u << 24)) __trap();
      } while (v < 32u);
#pragma unroll
      for (int i = 0; i < 3; i++) {
        const int pi = tid + 128 * i, d = pi / 12, e = (pi - d * 12) * 2;
        float sx = 0.f, sy = 0.f;
        if (d < 20) {
          const float* src = g_kvpart + (size_t)h * NMT * 480 + d * 24 + e;
#pragma unroll
          for (int m = 0; m < 16; m++) { float2 t = __ldcg(reinterpret_cast<const float2*>(src + m * 480)); sx += t.x; sy += t.y; }
        }
        *reinterpret_cast<uint32_t*>(sgen + 16 * AT_KV + (e >> 3) * 512 + d * 16 + (e & 7) * 2) = pack_bf16(sx, sy);
      }
      fence_proxy_async();
      mbar_arrive(kvbReady);
    }
    const int grow = mt * 128 + row;
    const float g0 = g_gate[grow], g1 = g_gate[grow + 8];
    uint8_t* dst = g_OC + (size_t)mt * 160 * CHB + row * 16;
    {
      const float l0 = __shfl_sync(~0u, o[8], (lane & ~3) | 2), l1 = __shfl_sync(~0u, o[10], (lane & ~3) | 2);
      store_o(o, (1.0f - g0) / l0, (1.0f - g1) / l1, dst, 640 + h * 20, c);
    }
    {
      const uint8_t* psrc = g_PQA + (size_t)(h * NMT + mt) * HB + row * 16 + c * 4;
      uint32_t a0 = *reinterpret_cast<const uint32_t*>(psrc), a1 = *reinterpret_cast<const uint32_t*>(psrc + 128);
      uint32_t a2 = *reinterpret_cast<const uint32_t*>(psrc + CHB), a3 = *reinterpret_cast<const uint32_t*>(psrc + CHB + 128);
      uint32_t b0 = 0, b1 = 0;
      if (c < 2) { b0 = *reinterpret_cast<const uint32_t*>(psrc + 2 * CHB); b1 = *reinterpret_cast<const uint32_t*>(psrc + 2 * CHB + 128); }
      float oa[12];
      mbar_wait(kvbReady, 0);
      WG_FENCE();
      wgmma_n24_rs_tb_init(oa, a0, a1, a2, a3, make_desc(sKVB, 128, 512, 0));
      wgmma_n24_rs_tb(oa, b0, b1, 0u, 0u, make_desc(sKVB + 256, 128, 512, 0), 1);
      WG_COMMIT();
      WG_WAIT(0);
      fence_regs(oa);
      const float d0 = __shfl_sync(~0u, oa[8], (lane & ~3) | 2) + 1e-6f, d1 = __shfl_sync(~0u, oa[10], (lane & ~3) | 2) + 1e-6f;
      store_o(oa, g0 / d0, g1 / d1, dst, h * 20, c);
    }
  }
}

constexpr int G3_ST = 5;
constexpr int G3_STAGE = 16384 + 20480;
constexpr int G3_SMEM = G3_ST * G3_STAGE + 256 + 1024;

__global__ void __cluster_dims__(2, 1, 1) __launch_bounds__(288, 1)
gemm_out_kernel(const __grid_constant__ CUtensorMap tmWoA, const __grid_constant__ CUtensorMap tmWoB,
                __nv_bfloat16* __restrict__ out) {
  extern __shared__ uint8_t smem_raw[];
  const uint32_t sbase = (smem_u32(smem_raw) + 1023) & ~1023u;
  uint8_t* sgen = smem_raw + (sbase - smem_u32(smem_raw));
  const uint32_t sBar = sbase + G3_ST * G3_STAGE;
  const uint32_t full = sBar, empty = sBar + 8 * G3_ST;
  const int tid = threadIdx.x, warp = __shfl_sync(~0u, tid >> 5, 0), lane = tid & 31;
  const int rank = blockIdx.x & 1, tile = blockIdx.x >> 1, mt = tile >> 2, nt = tile & 3;
  if (tid == 0) {
    for (int i = 0; i < G3_ST; i++) { mbar_init(full + 8 * i, 1); mbar_init(empty + 8 * i, 8); }
    fence_barrier_init();
  }
  if (blockIdx.x == 0 && tid < NH) g_kvflag[tid] = 0;
  __syncthreads();
  float acc[80];
  const int wg = warp >> 2, w4 = warp & 3;
  if (warp == 8) {
    if (lane == 0) {
      const CUtensorMap* tmW = rank ? &tmWoB : &tmWoA;
      const uint8_t* asrc = g_OC + (size_t)(mt * 160 + rank * 80) * CHB;
      for (int kb = 0; kb < 10; kb++) {
        const int s = kb % G3_ST;
        mbar_wait(empty + 8 * s, ((kb / G3_ST) & 1) ^ 1);
        mbar_expect_tx(full + 8 * s, G3_STAGE);
        bulk_load(sbase + s * G3_STAGE, asrc + (size_t)kb * 16384, 16384, full + 8 * s);
        tma_load_3d(sbase + s * G3_STAGE + 16384, tmW, 0, kb * 64, nt * 5, full + 8 * s);
      }
    }
  } else {
    for (int kb = 0; kb < 10; kb++) {
      const int s = kb % G3_ST;
      mbar_wait(full + 8 * s, (kb / G3_ST) & 1);
      WG_FENCE();
#pragma unroll
      for (int kk = 0; kk < 4; kk++) {
        uint64_t da = make_desc(sbase + s * G3_STAGE + kk * 2 * CHB + wg * 1024, CHB, 128, 0);
        uint64_t db = make_desc(sbase + s * G3_STAGE + 16384 + kk * 1024, 4096, 512, 2);
        wgmma_n160_ss_tb(acc, da, db, (kb | kk) != 0);
      }
      WG_COMMIT();
      if (kb > 0) {
        WG_WAIT(1);
        if (lane == 0) mbar_arrive(empty + 8 * ((kb - 1) % G3_ST));
      }
    }
    WG_WAIT(0);
    fence_regs(acc);
  }
  asm volatile("barrier.cluster.arrive.release.aligned;\nbarrier.cluster.wait.acquire.aligned;" ::: "memory");
  if (warp < 8) {
    uint32_t dst = sbase + (uint32_t)tid * 16, rdst;
    asm volatile("mapa.shared::cluster.u32 %0, %1, %2;" : "=r"(rdst) : "r"(dst), "r"(rank ^ 1));
#pragma unroll
    for (int i = 0; i < 10; i++) {
      float a, b, cc, d;
      if (rank == 0) { a = acc[40 + 4 * i]; b = acc[41 + 4 * i]; cc = acc[42 + 4 * i]; d = acc[43 + 4 * i]; }
      else { a = acc[4 * i]; b = acc[4 * i + 1]; cc = acc[4 * i + 2]; d = acc[4 * i + 3]; }
      asm volatile("st.shared::cluster.v4.f32 [%0], {%1,%2,%3,%4};" ::"r"(rdst + i * 4096), "f"(a), "f"(b), "f"(cc), "f"(d) : "memory");
    }
  }
  asm volatile("barrier.cluster.arrive.release.aligned;\nbarrier.cluster.wait.acquire.aligned;" ::: "memory");
  if (warp < 8) {
    const int row = mt * 128 + wg * 64 + w4 * 16 + (lane >> 2);
    __nv_bfloat16* o0 = out + (size_t)row * DM + nt * 160 + rank * 80 + (lane & 3) * 2;
#pragma unroll
    for (int i = 0; i < 10; i++) {
      float4 r = *reinterpret_cast<const float4*>(sgen + tid * 16 + i * 4096);
      float a, b, cc, d;
      if (rank == 0) { a = acc[4 * i]; b = acc[4 * i + 1]; cc = acc[4 * i + 2]; d = acc[4 * i + 3]; }
      else { a = acc[40 + 4 * i]; b = acc[41 + 4 * i]; cc = acc[42 + 4 * i]; d = acc[43 + 4 * i]; }
      *reinterpret_cast<uint32_t*>(o0 + 8 * i) = pack_bf16(a + r.x, b + r.y);
      *reinterpret_cast<uint32_t*>(o0 + 8 * DM + 8 * i) = pack_bf16(cc + r.z, d + r.w);
    }
  }
}

typedef CUresult (*EncodeFn)(CUtensorMap*, CUtensorMapDataType, cuuint32_t, void*, const cuuint64_t*, const cuuint64_t*,
                             const cuuint32_t*, const cuuint32_t*, CUtensorMapInterleave, CUtensorMapSwizzle,
                             CUtensorMapL2promotion, CUtensorMapFloatOOBfill);

void make_w_map(EncodeFn enc, CUtensorMap* tm, const void* w, int ncols) {
  cuuint64_t dims[3] = {32, 640, (cuuint64_t)(ncols / 32)};
  cuuint64_t strides[2] = {(cuuint64_t)ncols * 2, 64};
  cuuint32_t box[3] = {32, 64, 5};
  cuuint32_t es[3] = {1, 1, 1};
  enc(tm, CU_TENSOR_MAP_DATA_TYPE_BFLOAT16, 3, const_cast<void*>(w), dims, strides, box, es, CU_TENSOR_MAP_INTERLEAVE_NONE,
      CU_TENSOR_MAP_SWIZZLE_64B, CU_TENSOR_MAP_L2_PROMOTION_L2_128B, CU_TENSOR_MAP_FLOAT_OOB_FILL_NONE);
}

}

extern "C" void kernel_launch(void* const* d_in, const int* in_sizes, int n_in, void* d_out, int out_size) {
  const __nv_bfloat16* x = (const __nv_bfloat16*)d_in[0];
  const void* wqkvA = d_in[1];
  const void* woA = d_in[2];
  const void* wqkvB = d_in[4];
  const void* woB = d_in[5];
  const __nv_bfloat16* gate_w = (const __nv_bfloat16*)d_in[6];

  static EncodeFn enc = nullptr;
  if (!enc) {
    void* fn = nullptr;
    cudaDriverEntryPointQueryResult st;
    cudaGetDriverEntryPoint("cuTensorMapEncodeTiled", &fn, cudaEnableDefault, &st);
    enc = (EncodeFn)fn;
    cudaFuncSetAttribute(gemm_qkv_kernel, cudaFuncAttributeMaxDynamicSharedMemorySize, G1_SMEM);
    cudaFuncSetAttribute(attn_kernel, cudaFuncAttributeMaxDynamicSharedMemorySize, AT_SMEM);
    cudaFuncSetAttribute(gemm_out_kernel, cudaFuncAttributeMaxDynamicSharedMemorySize, G3_SMEM);
  }
  CUtensorMap tmX, tmWA, tmWB, tmWoA, tmWoB;
  {
    cuuint64_t dims[2] = {640, 2048};
    cuuint64_t strides[1] = {1280};
    cuuint32_t box[2] = {64, 128};
    cuuint32_t es[2] = {1, 1};
    enc(&tmX, CU_TENSOR_MAP_DATA_TYPE_BFLOAT16, 2, (void*)x, dims, strides, box, es, CU_TENSOR_MAP_INTERLEAVE_NONE,
        CU_TENSOR_MAP_SWIZZLE_128B, CU_TENSOR_MAP_L2_PROMOTION_L2_128B, CU_TENSOR_MAP_FLOAT_OOB_FILL_NONE);
  }
  make_w_map(enc, &tmWA, wqkvA, 1920);
  make_w_map(enc, &tmWB, wqkvB, 1920);
  make_w_map(enc, &tmWoA, woA, 640);
  make_w_map(enc, &tmWoB, woB, 640);

  cudaStream_t st = cudaStreamPerThread;
  const int stages = 7;
  if (stages & 1) gemm_qkv_kernel<<<128, 512, G1_SMEM, st>>>(tmX, tmWA, tmWB, x, gate_w);
  if (stages & 2) attn_kernel<<<128, 512, AT_SMEM, st>>>();
  if (stages & 4) gemm_out_kernel<<<128, 288, G3_SMEM, st>>>(tmWoA, tmWoB, (__nv_bfloat16*)d_out);
}
```

```cpp
#include <cuda_runtime.h>
#include <cuda_bf16.h>
#include <cuda.h>
#include <stdint.h>

namespace {

constexpr int SEQ = 2048, DM = 640, NH = 32, NMT = 16;
constexpr int HB = 6144;
constexpr int CHB = 2048;
constexpr float QSCALE = 0.22360679774997896f * 1.4426950408889634f;

constexpr uint32_t MUFU_MASK = 0x4949u | 0x0000u;
constexpr float FAST_M_LIMIT = 60.0f;

__device__ __align__(1024) uint8_t g_QB[NH * NMT * HB];
__device__ __align__(1024) uint8_t g_KVB[NH * NMT * 2 * HB];
__device__ __align__(1024) uint8_t g_PQA[NH * NMT * HB];
__device__ __align__(1024) uint8_t g_KVA[NH * NMT * 2 * HB];
__device__ __align__(1024) uint8_t g_OC[NMT * 160 * CHB];
__device__ float g_nrmQ[NH * 128];
__device__ float g_nrmK[NH * 128];
__device__ float g_gate[SEQ];
__device__ __align__(16) float g_kvpart[NH * NMT * 20 * 24];
__device__ unsigned g_kvflag[NH];

__device__ __forceinline__ uint32_t smem_u32(const void* p) { return (uint32_t)__cvta_generic_to_shared(p); }
__device__ __forceinline__ void mbar_init(uint32_t bar, uint32_t cnt) {
  asm volatile("mbarrier.init.shared::cta.b64 [%0], %1;" ::"r"(bar), "r"(cnt) : "memory");
}
__device__ __forceinline__ void mbar_expect_tx(uint32_t bar, uint32_t bytes) {
  asm volatile("mbarrier.arrive.expect_tx.shared::cta.b64 _, [%0], %1;" ::"r"(bar), "r"(bytes) : "memory");
}
__device__ __forceinline__ void mbar_arrive(uint32_t bar) {
  asm volatile("mbarrier.arrive.shared::cta.b64 _, [%0];" ::"r"(bar) : "memory");
}
__device__ __forceinline__ void mbar_wait(uint32_t bar, uint32_t parity) {
  asm volatile(
      "{\n.reg .pred p;\n.reg .u32 n;\nmov.u32 n, 0;\n"
      "MW_LOOP:\nmbarrier.try_wait.parity.shared::cta.b64 p, [%0], %1;\n@p bra MW_DONE;\n"
      "add.u32 n, n, 1;\nsetp.lt.u32 p, n, 4194304;\n@p bra MW_LOOP;\ntrap;\nMW_DONE:\n}\n" ::"r"(bar), "r"(parity)
      : "memory");
}
__device__ __forceinline__ void fence_barrier_init() { asm volatile("fence.mbarrier_init.release.cluster;" ::: "memory"); }
__device__ __forceinline__ void fence_proxy_async() { asm volatile("fence.proxy.async;" ::: "memory"); }
__device__ __forceinline__ void bulk_load(uint32_t dst, const void* src, uint32_t bytes, uint32_t bar) {
  asm volatile("cp.async.bulk.shared::cluster.global.mbarrier::complete_tx::bytes [%0], [%1], %2, [%3];"
               ::"r"(dst), "l"(src), "r"(bytes), "r"(bar) : "memory");
}
__device__ __forceinline__ void tma_load_2d(uint32_t dst, const CUtensorMap* tm, int c0, int c1, uint32_t bar) {
  asm volatile("cp.async.bulk.tensor.2d.shared::cluster.global.mbarrier::complete_tx::bytes [%0], [%1, {%3, %4}], [%2];"
               ::"r"(dst), "l"(tm), "r"(bar), "r"(c0), "r"(c1) : "memory");
}
__device__ __forceinline__ void tma_load_3d(uint32_t dst, const CUtensorMap* tm, int c0, int c1, int c2, uint32_t bar) {
  asm volatile("cp.async.bulk.tensor.3d.shared::cluster.global.mbarrier::complete_tx::bytes [%0], [%1, {%3, %4, %5}], [%2];"
               ::"r"(dst), "l"(tm), "r"(bar), "r"(c0), "r"(c1), "r"(c2) : "memory");
}
__device__ __forceinline__ void prefetch_tmap(const CUtensorMap* tm) {
  asm volatile("prefetch.tensormap [%0];" ::"l"(tm) : "memory");
}
__device__ __forceinline__ uint32_t desc_lo(uint32_t saddr, uint32_t lbo) { return ((saddr & 0x3FFFF) >> 4) | ((lbo >> 4) << 16); }
__host__ __device__ constexpr uint32_t desc_hi(uint32_t sbo, uint32_t swz) { return (sbo >> 4) | (swz << 30); }
#define WG_FENCE() asm volatile("wgmma.fence.sync.aligned;" ::: "memory")
#define WG_COMMIT() asm volatile("wgmma.commit_group.sync.aligned;" ::: "memory")
#define WG_WAIT(n) asm volatile("wgmma.wait_group.sync.aligned %0;" ::"n"(n) : "memory")
template <int N>
__device__ __forceinline__ void fence_regs(float (&d)[N]) {
#pragma unroll
  for (int i = 0; i < N; i++) asm volatile("" : "+f"(d[i])::"memory");
}
template <int N>
__device__ __forceinline__ void fence_regs_u(uint32_t (&d)[N]) {
#pragma unroll
  for (int i = 0; i < N; i++) asm volatile("" : "+r"(d[i])::"memory");
}
__device__ __forceinline__ uint32_t pack_bf16(float lo, float hi) {
  uint32_t r;
  asm("cvt.rn.bf16x2.f32 %0, %1, %2;" : "=r"(r) : "f"(hi), "f"(lo));
  return r;
}
__device__ __forceinline__ float ex2f(float x) {
  float r;
  asm("ex2.approx.ftz.f32 %0, %1;" : "=f"(r) : "f"(x));
  return r;
}
__device__ __forceinline__ float bf_lo(uint32_t v) { return __uint_as_float(v << 16); }
__device__ __forceinline__ float bf_hi(uint32_t v) { return __uint_as_float(v & 0xFFFF0000u); }
__device__ __forceinline__ uint32_t hfma2(uint32_t a, uint32_t b, uint32_t c) {
  uint32_t r;
  asm("fma.rn.f16x2 %0, %1, %2, %3;" : "=r"(r) : "r"(a), "r"(b), "r"(c));
  return r;
}

__device__ __forceinline__ void wgmma_n160_ss_tb(float (&d)[80], uint32_t alo, uint32_t ahi, uint32_t blo, uint32_t bhi, int sc) {
  asm volatile("{\n.reg .pred p;\n.reg .b64 da, db;\nmov.b64 da, {%80, %81};\nmov.b64 db, {%82, %83};\nsetp.ne.b32 p, %84, 0;\n"
  "wgmma.mma_async.sync.aligned.m64n160k16.f32.bf16.bf16 {%0,%1,%2,%3,%4,%5,%6,%7,%8,%9,%10,%11,%12,%13,%14,%15,%16,%17,%18,%19,%20,%21,%22,%23,%24,%25,%26,%27,%28,%29,%30,%31,%32,%33,%34,%35,%36,%37,%38,%39,%40,%41,%42,%43,%44,%45,%46,%47,%48,%49,%50,%51,%52,%53,%54,%55,%56,%57,%58,%59,%60,%61,%62,%63,%64,%65,%66,%67,%68,%69,%70,%71,%72,%73,%74,%75,%76,%77,%78,%79}, da, db, p, 1, 1, 0, 1;\n}\n"
   : "+f"(d[0]),"+f"(d[1]),"+f"(d[2]),"+f"(d[3]),"+f"(d[4]),"+f"(d[5]),"+f"(d[6]),"+f"(d[7]),"+f"(d[8]),"+f"(d[9]),"+f"(d[10]),"+f"(d[11]),"+f"(d[12]),"+f"(d[13]),"+f"(d[14]),"+f"(d[15]),"+f"(d[16]),"+f"(d[17]),"+f"(d[18]),"+f"(d[19]),"+f"(d[20]),"+f"(d[21]),"+f"(d[22]),"+f"(d[23]),"+f"(d[24]),"+f"(d[25]),"+f"(d[26]),"+f"(d[27]),"+f"(d[28]),"+f"(d[29]),"+f"(d[30]),"+f"(d[31]),"+f"(d[32]),"+f"(d[33]),"+f"(d[34]),"+f"(d[35]),"+f"(d[36]),"+f"(d[37]),"+f"(d[38]),"+f"(d[39]),"+f"(d[40]),"+f"(d[41]),"+f"(d[42]),"+f"(d[43]),"+f"(d[44]),"+f"(d[45]),"+f"(d[46]),"+f"(d[47]),"+f"(d[48]),"+f"(d[49]),"+f"(d[50]),"+f"(d[51]),"+f"(d[52]),"+f"(d[53]),"+f"(d[54]),"+f"(d[55]),"+f"(d[56]),"+f"(d[57]),"+f"(d[58]),"+f"(d[59]),"+f"(d[60]),"+f"(d[61]),"+f"(d[62]),"+f"(d[63]),"+f"(d[64]),"+f"(d[65]),"+f"(d[66]),"+f"(d[67]),"+f"(d[68]),"+f"(d[69]),"+f"(d[70]),"+f"(d[71]),"+f"(d[72]),"+f"(d[73]),"+f"(d[74]),"+f"(d[75]),"+f"(d[76]),"+f"(d[77]),"+f"(d[78]),"+f"(d[79])
   : "r"(alo),"r"(ahi),"r"(blo),"r"(bhi),"r"(sc));
}
__device__ __forceinline__ void wgmma_n128_rs_init(float (&d)[64], uint32_t a0, uint32_t a1, uint32_t a2, uint32_t a3, uint32_t blo, uint32_t bhi) {
  asm volatile("{\n.reg .pred p;\n.reg .b64 da, db;\nmov.b64 db, {%68, %69};\nsetp.ne.b32 p, 0, 0;\n"
  "wgmma.mma_async.sync.aligned.m64n128k16.f32.bf16.bf16 {%0,%1,%2,%3,%4,%5,%6,%7,%8,%9,%10,%11,%12,%13,%14,%15,%16,%17,%18,%19,%20,%21,%22,%23,%24,%25,%26,%27,%28,%29,%30,%31,%32,%33,%34,%35,%36,%37,%38,%39,%40,%41,%42,%43,%44,%45,%46,%47,%48,%49,%50,%51,%52,%53,%54,%55,%56,%57,%58,%59,%60,%61,%62,%63}, {%64,%65,%66,%67}, db, p, 1, 1, 0;\n}\n"
   : "=f"(d[0]),"=f"(d[1]),"=f"(d[2]),"=f"(d[3]),"=f"(d[4]),"=f"(d[5]),"=f"(d[6]),"=f"(d[7]),"=f"(d[8]),"=f"(d[9]),"=f"(d[10]),"=f"(d[11]),"=f"(d[12]),"=f"(d[13]),"=f"(d[14]),"=f"(d[15]),"=f"(d[16]),"=f"(d[17]),"=f"(d[18]),"=f"(d[19]),"=f"(d[20]),"=f"(d[21]),"=f"(d[22]),"=f"(d[23]),"=f"(d[24]),"=f"(d[25]),"=f"(d[26]),"=f"(d[27]),"=f"(d[28]),"=f"(d[29]),"=f"(d[30]),"=f"(d[31]),"=f"(d[32]),"=f"(d[33]),"=f"(d[34]),"=f"(d[35]),"=f"(d[36]),"=f"(d[37]),"=f"(d[38]),"=f"(d[39]),"=f"(d[40]),"=f"(d[41]),"=f"(d[42]),"=f"(d[43]),"=f"(d[44]),"=f"(d[45]),"=f"(d[46]),"=f"(d[47]),"=f"(d[48]),"=f"(d[49]),"=f"(d[50]),"=f"(d[51]),"=f"(d[52]),"=f"(d[53]),"=f"(d[54]),"=f"(d[55]),"=f"(d[56]),"=f"(d[57]),"=f"(d[58]),"=f"(d[59]),"=f"(d[60]),"=f"(d[61]),"=f"(d[62]),"=f"(d[63])
   : "r"(a0),"r"(a1),"r"(a2),"r"(a3),"r"(blo),"r"(bhi));
}
__device__ __forceinline__ void wgmma_n128_rs_acc(float (&d)[64], uint32_t a0, uint32_t a1, uint32_t a2, uint32_t a3, uint32_t blo, uint32_t bhi) {
  asm volatile("{\n.reg .pred p;\n.reg .b64 da, db;\nmov.b64 db, {%68, %69};\nsetp.eq.b32 p, 0, 0;\n"
  "wgmma.mma_async.sync.aligned.m64n128k16.f32.bf16.bf16 {%0,%1,%2,%3,%4,%5,%6,%7,%8,%9,%10,%11,%12,%13,%14,%15,%16,%17,%18,%19,%20,%21,%22,%23,%24,%25,%26,%27,%28,%29,%30,%31,%32,%33,%34,%35,%36,%37,%38,%39,%40,%41,%42,%43,%44,%45,%46,%47,%48,%49,%50,%51,%52,%53,%54,%55,%56,%57,%58,%59,%60,%61,%62,%63}, {%64,%65,%66,%67}, db, p, 1, 1, 0;\n}\n"
   : "+f"(d[0]),"+f"(d[1]),"+f"(d[2]),"+f"(d[3]),"+f"(d[4]),"+f"(d[5]),"+f"(d[6]),"+f"(d[7]),"+f"(d[8]),"+f"(d[9]),"+f"(d[10]),"+f"(d[11]),"+f"(d[12]),"+f"(d[13]),"+f"(d[14]),"+f"(d[15]),"+f"(d[16]),"+f"(d[17]),"+f"(d[18]),"+f"(d[19]),"+f"(d[20]),"+f"(d[21]),"+f"(d[22]),"+f"(d[23]),"+f"(d[24]),"+f"(d[25]),"+f"(d[26]),"+f"(d[27]),"+f"(d[28]),"+f"(d[29]),"+f"(d[30]),"+f"(d[31]),"+f"(d[32]),"+f"(d[33]),"+f"(d[34]),"+f"(d[35]),"+f"(d[36]),"+f"(d[37]),"+f"(d[38]),"+f"(d[39]),"+f"(d[40]),"+f"(d[41]),"+f"(d[42]),"+f"(d[43]),"+f"(d[44]),"+f"(d[45]),"+f"(d[46]),"+f"(d[47]),"+f"(d[48]),"+f"(d[49]),"+f"(d[50]),"+f"(d[51]),"+f"(d[52]),"+f"(d[53]),"+f"(d[54]),"+f"(d[55]),"+f"(d[56]),"+f"(d[57]),"+f"(d[58]),"+f"(d[59]),"+f"(d[60]),"+f"(d[61]),"+f"(d[62]),"+f"(d[63])
   : "r"(a0),"r"(a1),"r"(a2),"r"(a3),"r"(blo),"r"(bhi));
}
__device__ __forceinline__ void wgmma_n64_rs_init(float (&d)[32], uint32_t a0, uint32_t a1, uint32_t a2, uint32_t a3, uint32_t blo, uint32_t bhi) {
  asm volatile("{\n.reg .pred p;\n.reg .b64 da, db;\nmov.b64 db, {%36, %37};\nsetp.ne.b32 p, 0, 0;\n"
  "wgmma.mma_async.sync.aligned.m64n64k16.f32.bf16.bf16 {%0,%1,%2,%3,%4,%5,%6,%7,%8,%9,%10,%11,%12,%13,%14,%15,%16,%17,%18,%19,%20,%21,%22,%23,%24,%25,%26,%27,%28,%29,%30,%31}, {%32,%33,%34,%35}, db, p, 1, 1, 0;\n}\n"
   : "=f"(d[0]),"=f"(d[1]),"=f"(d[2]),"=f"(d[3]),"=f"(d[4]),"=f"(d[5]),"=f"(d[6]),"=f"(d[7]),"=f"(d[8]),"=f"(d[9]),"=f"(d[10]),"=f"(d[11]),"=f"(d[12]),"=f"(d[13]),"=f"(d[14]),"=f"(d[15]),"=f"(d[16]),"=f"(d[17]),"=f"(d[18]),"=f"(d[19]),"=f"(d[20]),"=f"(d[21]),"=f"(d[22]),"=f"(d[23]),"=f"(d[24]),"=f"(d[25]),"=f"(d[26]),"=f"(d[27]),"=f"(d[28]),"=f"(d[29]),"=f"(d[30]),"=f"(d[31])
   : "r"(a0),"r"(a1),"r"(a2),"r"(a3),"r"(blo),"r"(bhi));
}
__device__ __forceinline__ void wgmma_n64_rs_acc(float (&d)[32], uint32_t a0, uint32_t a1, uint32_t a2, uint32_t a3, uint32_t blo, uint32_t bhi) {
  asm volatile("{\n.reg .pred p;\n.reg .b64 da, db;\nmov.b64 db, {%36, %37};\nsetp.eq.b32 p, 0, 0;\n"
  "wgmma.mma_async.sync.aligned.m64n64k16.f32.bf16.bf16 {%0,%1,%2,%3,%4,%5,%6,%7,%8,%9,%10,%11,%12,%13,%14,%15,%16,%17,%18,%19,%20,%21,%22,%23,%24,%25,%26,%27,%28,%29,%30,%31}, {%32,%33,%34,%35}, db, p, 1, 1, 0;\n}\n"
   : "+f"(d[0]),"+f"(d[1]),"+f"(d[2]),"+f"(d[3]),"+f"(d[4]),"+f"(d[5]),"+f"(d[6]),"+f"(d[7]),"+f"(d[8]),"+f"(d[9]),"+f"(d[10]),"+f"(d[11]),"+f"(d[12]),"+f"(d[13]),"+f"(d[14]),"+f"(d[15]),"+f"(d[16]),"+f"(d[17]),"+f"(d[18]),"+f"(d[19]),"+f"(d[20]),"+f"(d[21]),"+f"(d[22]),"+f"(d[23]),"+f"(d[24]),"+f"(d[25]),"+f"(d[26]),"+f"(d[27]),"+f"(d[28]),"+f"(d[29]),"+f"(d[30]),"+f"(d[31])
   : "r"(a0),"r"(a1),"r"(a2),"r"(a3),"r"(blo),"r"(bhi));
}
__device__ __forceinline__ void wgmma_n24_rs_tb(float (&d)[12], uint32_t a0, uint32_t a1, uint32_t a2, uint32_t a3, uint32_t blo, uint32_t bhi, int sc) {
  asm volatile("{\n.reg .pred p;\n.reg .b64 da, db;\nmov.b64 db, {%16, %17};\nsetp.ne.b32 p, %18, 0;\n"
  "wgmma.mma_async.sync.aligned.m64n24k16.f32.bf16.bf16 {%0,%1,%2,%3,%4,%5,%6,%7,%8,%9,%10,%11}, {%12,%13,%14,%15}, db, p, 1, 1, 1;\n}\n"
   : "+f"(d[0]),"+f"(d[1]),"+f"(d[2]),"+f"(d[3]),"+f"(d[4]),"+f"(d[5]),"+f"(d[6]),"+f"(d[7]),"+f"(d[8]),"+f"(d[9]),"+f"(d[10]),"+f"(d[11])
   : "r"(a0),"r"(a1),"r"(a2),"r"(a3),"r"(blo),"r"(bhi),"r"(sc));
}
__device__ __forceinline__ void wgmma_n24_rs_tb_init(float (&d)[12], uint32_t a0, uint32_t a1, uint32_t a2, uint32_t a3, uint32_t blo, uint32_t bhi) {
  asm volatile("{\n.reg .pred p;\n.reg .b64 da, db;\nmov.b64 db, {%16, %17};\nsetp.ne.b32 p, 0, 0;\n"
  "wgmma.mma_async.sync.aligned.m64n24k16.f32.bf16.bf16 {%0,%1,%2,%3,%4,%5,%6,%7,%8,%9,%10,%11}, {%12,%13,%14,%15}, db, p, 1, 1, 1;\n}\n"
   : "=f"(d[0]),"=f"(d[1]),"=f"(d[2]),"=f"(d[3]),"=f"(d[4]),"=f"(d[5]),"=f"(d[6]),"=f"(d[7]),"=f"(d[8]),"=f"(d[9]),"=f"(d[10]),"=f"(d[11])
   : "r"(a0),"r"(a1),"r"(a2),"r"(a3),"r"(blo),"r"(bhi));
}
__device__ __forceinline__ void wgmma_n24_rs_tb_acc(float (&d)[12], uint32_t a0, uint32_t a1, uint32_t a2, uint32_t a3, uint32_t blo, uint32_t bhi) {
  asm volatile("{\n.reg .pred p;\n.reg .b64 da, db;\nmov.b64 db, {%16, %17};\nsetp.eq.b32 p, 0, 0;\n"
  "wgmma.mma_async.sync.aligned.m64n24k16.f32.bf16.bf16 {%0,%1,%2,%3,%4,%5,%6,%7,%8,%9,%10,%11}, {%12,%13,%14,%15}, db, p, 1, 1, 1;\n}\n"
   : "+f"(d[0]),"+f"(d[1]),"+f"(d[2]),"+f"(d[3]),"+f"(d[4]),"+f"(d[5]),"+f"(d[6]),"+f"(d[7]),"+f"(d[8]),"+f"(d[9]),"+f"(d[10]),"+f"(d[11])
   : "r"(a0),"r"(a1),"r"(a2),"r"(a3),"r"(blo),"r"(bhi));
}
__device__ __forceinline__ void wgmma_n24_ss_tatb_init(float (&d)[12], uint32_t alo, uint32_t ahi, uint32_t blo, uint32_t bhi) {
  asm volatile("{\n.reg .pred p;\n.reg .b64 da, db;\nmov.b64 da, {%12, %13};\nmov.b64 db, {%14, %15};\nsetp.ne.b32 p, 0, 0;\n"
  "wgmma.mma_async.sync.aligned.m64n24k16.f32.bf16.bf16 {%0,%1,%2,%3,%4,%5,%6,%7,%8,%9,%10,%11}, da, db, p, 1, 1, 1, 1;\n}\n"
   : "=f"(d[0]),"=f"(d[1]),"=f"(d[2]),"=f"(d[3]),"=f"(d[4]),"=f"(d[5]),"=f"(d[6]),"=f"(d[7]),"=f"(d[8]),"=f"(d[9]),"=f"(d[10]),"=f"(d[11])
   : "r"(alo),"r"(ahi),"r"(blo),"r"(bhi));
}
__device__ __forceinline__ void wgmma_n24_ss_tatb_acc(float (&d)[12], uint32_t alo, uint32_t ahi, uint32_t blo, uint32_t bhi) {
  asm volatile("{\n.reg .pred p;\n.reg .b64 da, db;\nmov.b64 da, {%12, %13};\nmov.b64 db, {%14, %15};\nsetp.eq.b32 p, 0, 0;\n"
  "wgmma.mma_async.sync.aligned.m64n24k16.f32.bf16.bf16 {%0,%1,%2,%3,%4,%5,%6,%7,%8,%9,%10,%11}, da, db, p, 1, 1, 1, 1;\n}\n"
   : "+f"(d[0]),"+f"(d[1]),"+f"(d[2]),"+f"(d[3]),"+f"(d[4]),"+f"(d[5]),"+f"(d[6]),"+f"(d[7]),"+f"(d[8]),"+f"(d[9]),"+f"(d[10]),"+f"(d[11])
   : "r"(alo),"r"(ahi),"r"(blo),"r"(bhi));
}

constexpr int G1_A_BYTES = 10 * 16384;
constexpr int G1_BST = 5;
constexpr int G1_B_BYTES = 12288;
constexpr int G1_SMEM = G1_A_BYTES + G1_BST * G1_B_BYTES + 256 + 1024;

__device__ __forceinline__ float phi_fn(float t) { return (t > 0.f ? t + 1.0f : __expf(t)) + 1e-6f; }

template <int KIND>
__device__ __forceinline__ void g1_epilogue(float (&acc)[80], uint8_t* base, uint32_t hstride, int row, int lane,
                                            float* nrm  ) {
  const int c = lane & 3;
  uint32_t off[5];
#pragma unroll
  for (int bb = 0; bb < 5; bb++) {
    int col = 8 * bb + 2 * c;
    int hl = col >= 20 ? 1 : 0;
    int dim = col - 20 * hl;
    off[bb] = hl * hstride + (dim >> 3) * CHB + (dim & 7) * 2;
  }
  uint8_t* p0 = base + row * 16;
  uint2 pad0 = make_uint2(0, 0), pad1 = make_uint2(0, 0);
  if (KIND == 2) {
#pragma unroll
    for (int i = 0; i < 2; i++) {
      int r = row + 8 * i;
      bool mufu = (MUFU_MASK >> (r >> 3)) & 1;
      uint32_t s20, s21, s23;
      if (mufu) { s20 = 0; s21 = 0x4280; s23 = 0; }
      else if (r & 1) { s20 = 0x4680; s21 = 0x435A; s23 = 0x3F40; }
      else { s20 = 0x4680; s21 = 0x42FC; s23 = 0; }
      uint2 v = make_uint2(s20 | (s21 << 16), 0x3F80u | (s23 << 16));
      if (i == 0) pad0 = v; else pad1 = v;
    }
  } else if (KIND == 3) {
    pad0 = make_uint2(0x3F80u, 0); pad1 = pad0;
  }
#pragma unroll
  for (int p = 0; p < 4; p++) {
    float ne0 = 0.f, ne1 = 0.f, no0 = 0.f, no1 = 0.f;
#pragma unroll
    for (int bb = 0; bb < 5; bb++) {
      const int b = 5 * p + bb;
      float v0 = acc[4 * b], v1 = acc[4 * b + 1], v2 = acc[4 * b + 2], v3 = acc[4 * b + 3];
      if (KIND == 0) { v0 = phi_fn(v0); v1 = phi_fn(v1); v2 = phi_fn(v2); v3 = phi_fn(v3); }
      if (KIND == 1) { v0 *= QSCALE; v1 *= QSCALE; v2 *= QSCALE; v3 *= QSCALE; }
      uint32_t w0 = pack_bf16(v0, v1), w1 = pack_bf16(v2, v3);
      uint8_t* q = p0 + (size_t)(2 * p) * hstride + off[bb];
      *reinterpret_cast<uint32_t*>(q) = w0;
      *reinterpret_cast<uint32_t*>(q + 128) = w1;
      if (KIND == 1 || KIND == 2) {
        float s0 = bf_lo(w0) * bf_lo(w0) + bf_hi(w0) * bf_hi(w0);
        float s1 = bf_lo(w1) * bf_lo(w1) + bf_hi(w1) * bf_hi(w1);
        if (bb < 2) { ne0 += s0; ne1 += s1; }
        else if (bb > 2) { no0 += s0; no1 += s1; }
        else { if (c < 2) { ne0 += s0; ne1 += s1; } else { no0 += s0; no1 += s1; } }
      }
      if (KIND == 2 || KIND == 3) {
        if ((bb == 2 && c == 1) || (bb == 4 && c == 3)) {
          *reinterpret_cast<uint2*>(q + 4) = pad0;
          *reinterpret_cast<uint2*>(q + 4 + 128) = pad1;
        }
      }
    }
    if (KIND == 1 || KIND == 2) {
#pragma unroll
      for (int o = 1; o <= 2; o <<= 1) {
        ne0 += __shfl_xor_sync(~0u, ne0, o); ne1 += __shfl_xor_sync(~0u, ne1, o);
        no0 += __shfl_xor_sync(~0u, no0, o); no1 += __shfl_xor_sync(~0u, no1, o);
      }
      float me = fmaxf(ne0, ne1), mo = fmaxf(no0, no1);
#pragma unroll
      for (int o = 4; o <= 16; o <<= 1) {
        me = fmaxf(me, __shfl_xor_sync(~0u, me, o));
        mo = fmaxf(mo, __shfl_xor_sync(~0u, mo, o));
      }
      if (lane == 0) { nrm[(2 * p) * 128] = me; nrm[(2 * p + 1) * 128] = mo; }
    }
  }
}

__global__ void __launch_bounds__(512, 1)
gemm_qkv_kernel(const __grid_constant__ CUtensorMap tmX, const __grid_constant__ CUtensorMap tmWA,
                const __grid_constant__ CUtensorMap tmWB, const __nv_bfloat16* __restrict__ x,
                const __nv_bfloat16* __restrict__ gate_w) {
  extern __shared__ uint8_t smem_raw[];
  const uint32_t sbase = (smem_u32(smem_raw) + 1023) & ~1023u;
  const uint32_t sA = sbase, sB = sbase + G1_A_BYTES, sBar = sB + G1_BST * G1_B_BYTES;
  const uint32_t fullA = sBar, fullB = sBar + 80, emptyB = fullB + 8 * G1_BST, order = emptyB + 8 * G1_BST;
  const int tid = threadIdx.x, warp = __shfl_sync(~0u, tid >> 5, 0), lane = tid & 31;
  const int mt = blockIdx.x >> 3, j = blockIdx.x & 7;
  const int branch = j >> 2, jj = j & 3;
  const CUtensorMap* tmW = branch ? &tmWB : &tmWA;
  auto load_b = [&](int it) {
    const int t = it / 20, kb = it - t * 20, s = it % G1_BST;
    const int type = branch ? (t == 0 ? 1 : (t == 1 ? 0 : 2)) : t;
    const int c0 = type * 640 + jj * 160;
    mbar_expect_tx(fullB + 8 * s, G1_B_BYTES);
#pragma unroll
    for (int i = 0; i < 3; i++) tma_load_2d(sB + s * G1_B_BYTES + i * 4096, tmW, c0 + 64 * i, kb * 32, fullB + 8 * s);
  };
  if (tid == 0) {
    for (int i = 0; i < 10; i++) mbar_init(fullA + 8 * i, 1);
    for (int i = 0; i < G1_BST; i++) { mbar_init(fullB + 8 * i, 1); mbar_init(emptyB + 8 * i, 8); }
    mbar_init(order, 8); mbar_init(order + 8, 8);
    fence_barrier_init();
  }
  __syncthreads();
  if (tid == 256) {
    for (int kb = 0; kb < 10; kb++) {
      mbar_expect_tx(fullA + 8 * kb, 16384);
      tma_load_2d(sA + kb * 16384, &tmX, kb * 64, mt * 128, fullA + 8 * kb);
      if (2 * kb < G1_BST) load_b(2 * kb);
      if (2 * kb + 1 < G1_BST) load_b(2 * kb + 1);
    }
  }
  __syncwarp();
  const int grp = warp >> 3, wg = (warp >> 2) & 1, w4 = warp & 3;
  const bool elected = (tid & 255) == 0;
  if (grp == 1) {
    const int w8 = warp - 8;
#pragma unroll
    for (int rr = 0; rr < 2; rr++) {
      const int row = mt * 128 + j * 16 + w8 * 2 + rr;
      const uint2* xp = reinterpret_cast<const uint2*>(x + (size_t)row * DM);
      const uint2* gp = reinterpret_cast<const uint2*>(gate_w);
      float s = 0.f;
#pragma unroll
      for (int i = 0; i < 5; i++) {
        uint2 a = __ldg(xp + lane + 32 * i), g = __ldg(gp + lane + 32 * i);
        s += bf_lo(a.x) * bf_lo(g.x) + bf_hi(a.x) * bf_hi(g.x) + bf_lo(a.y) * bf_lo(g.y) + bf_hi(a.y) * bf_hi(g.y);
      }
#pragma unroll
      for (int o = 16; o >= 1; o >>= 1) s += __shfl_xor_sync(~0u, s, o);
      if (lane == 0) g_gate[row] = 1.0f / (1.0f + __expf(-s));
    }
  }
  float acc[80];
  const uint32_t a_lo0 = desc_lo(sA + wg * 8192, 16), b_lo0 = desc_lo(sB, 4096);
  constexpr uint32_t a_hi = desc_hi(1024, 1), b_hi = desc_hi(1024, 1);
  for (int t = grp; t < 3; t += 2) {
    if (t > 0) mbar_wait(order + 8 * (t - 1), 0);
    for (int kb = 0; kb < 20; kb++) {
      const int it = t * 20 + kb, s = it % G1_BST;
      if (t == 0 && !(kb & 1)) mbar_wait(fullA + 8 * (kb >> 1), 0);
      mbar_wait(fullB + 8 * s, (it / G1_BST) & 1);
      if (kb == 19 && t < 2 && lane == 0) mbar_arrive(order + 8 * t);
      const uint32_t alo = a_lo0 + (kb >> 1) * 1024 + (kb & 1) * 4, blo = b_lo0 + s * (G1_B_BYTES >> 4);
      WG_FENCE();
      wgmma_n160_ss_tb(acc, alo, a_hi, blo, b_hi, kb != 0);
      wgmma_n160_ss_tb(acc, alo + 2, a_hi, blo + 128, b_hi, 1);
      WG_COMMIT();
      if (kb > 0) {
        WG_WAIT(1);
        const int ip = it - 1;
        if (lane == 0) mbar_arrive(emptyB + 8 * (ip % G1_BST));
        if (elected && ip + G1_BST < 60) {
          mbar_wait(emptyB + 8 * (ip % G1_BST), (ip / G1_BST) & 1);
          load_b(ip + G1_BST);
        }
        __syncwarp();
      }
    }
    WG_WAIT(0);
    fence_regs(acc);
    {
      const int ip = t * 20 + 19;
      if (lane == 0) mbar_arrive(emptyB + 8 * (ip % G1_BST));
      if (elected && ip + G1_BST < 60) {
        mbar_wait(emptyB + 8 * (ip % G1_BST), (ip / G1_BST) & 1);
        load_b(ip + G1_BST);
      }
      __syncwarp();
    }
    const int type = branch ? (t == 0 ? 1 : (t == 1 ? 0 : 2)) : t;
    const int h0 = jj * 8;
    const int row = wg * 64 + w4 * 16 + (lane >> 2);
    const int grp16 = mt * 8 + wg * 4 + w4;
    if (branch == 0) {
      if (type == 0) g1_epilogue<0>(acc, g_PQA + (size_t)(h0 * NMT + mt) * HB, NMT * HB, row, lane, nullptr);
      else if (type == 1) g1_epilogue<0>(acc, g_KVA + (size_t)(h0 * NMT + mt) * 2 * HB, NMT * 2 * HB, row, lane, nullptr);
      else g1_epilogue<3>(acc, g_KVA + (size_t)(h0 * NMT + mt) * 2 * HB + HB, NMT * 2 * HB, row, lane, nullptr);
    } else {
      if (type == 0) g1_epilogue<1>(acc, g_QB + (size_t)(h0 * NMT + mt) * HB, NMT * HB, row, lane, g_nrmQ + h0 * 128 + grp16);
      else if (type == 1) g1_epilogue<2>(acc, g_KVB + (size_t)(h0 * NMT + mt) * 2 * HB, NMT * 2 * HB, row, lane, g_nrmK + h0 * 128 + grp16);
      else g1_epilogue<3>(acc, g_KVB + (size_t)(h0 * NMT + mt) * 2 * HB + HB, NMT * 2 * HB, row, lane, nullptr);
    }
  }
}

constexpr int AT_KV = 2 * HB;
constexpr int AT_SMEM = 16 * AT_KV + 1536 + 256 + 1024;

struct PolyConst { uint32_t mlo, one, mhi, c3; };
__device__ __forceinline__ uint32_t exp2_poly_pair(float t0, float t1, const PolyConst& k) {
  uint32_t u = __float_as_uint(t1) * 65536u + __float_as_uint(t0);
  uint32_t y;
  asm("lop3.b32 %0, %1, 0x01FF01FF, %2, 0xEA;" : "=r"(y) : "r"(u), "r"(k.one));
  uint32_t nf = u & 0xFE00FE00u;
  uint32_t q = hfma2(k.c3, y, 0x93BC93BCu);
  q = hfma2(q, y, 0x15D415D4u);
  q = hfma2(q, y, 0x1FE31FE3u);
  return (nf >> 2) + q;
}

__device__ __forceinline__ void store_o(float (&o)[12], float sc0, float sc1, uint8_t* dst  , int colbase, int c) {
#pragma unroll
  for (int b = 0; b < 3; b++) {
    int dim = 8 * b + 2 * c;
    if (dim < 20) {
      int col = colbase + dim;
      uint8_t* q = dst + (col >> 3) * CHB + (col & 7) * 2;
      *reinterpret_cast<uint32_t*>(q) = pack_bf16(o[4 * b] * sc0, o[4 * b + 1] * sc0);
      *reinterpret_cast<uint32_t*>(q + 128) = pack_bf16(o[4 * b + 2] * sc1, o[4 * b + 3] * sc1);
    }
  }
}

struct Frag6 { uint32_t a0, a1, a2, a3, b0, b1; };
__device__ __forceinline__ Frag6 load_frag(const uint8_t* src  , int c) {
  Frag6 f;
  f.a0 = *reinterpret_cast<const uint32_t*>(src); f.a1 = *reinterpret_cast<const uint32_t*>(src + 128);
  f.a2 = *reinterpret_cast<const uint32_t*>(src + CHB); f.a3 = *reinterpret_cast<const uint32_t*>(src + CHB + 128);
  f.b0 = 0; f.b1 = 0;
  if (c < 2) { f.b0 = *reinterpret_cast<const uint32_t*>(src + 2 * CHB); f.b1 = *reinterpret_cast<const uint32_t*>(src + 2 * CHB + 128); }
  return f;
}

struct AttnCtx {
  uint32_t sKV, full, kvaFull, kvbReady;
  uint8_t* sgen;
  unsigned* sCnt;
  const CUtensorMap* tmKV;
  int h, rb, wg, w4, lane, tid;
};

constexpr uint32_t KD_HI = desc_hi(128, 0);
constexpr uint32_t VD_HI = desc_hi(CHB, 0);

__device__ __forceinline__ void kv_partial(const AttnCtx& x) {
  float kv[12];
  mbar_wait(x.kvaFull, 0);
  const uint32_t alo = desc_lo(x.sKV + (11 + x.wg) * AT_KV, 128), blo = alo + (HB >> 4);
  WG_FENCE();
  wgmma_n24_ss_tatb_init(kv, alo, VD_HI, blo, VD_HI);
#pragma unroll
  for (int kk = 1; kk < 8; kk++) wgmma_n24_ss_tatb_acc(kv, alo + kk * 16, VD_HI, blo + kk * 16, VD_HI);
  WG_COMMIT();
  WG_WAIT(0);
  fence_regs(kv);
  if (x.lane == 0) {
    unsigned old = atomicAdd(x.sCnt, 1u);
    if (old == 15) {
      fence_proxy_async();
      for (int i = 11; i < 15; i++) {
        mbar_expect_tx(x.full + 8 * i, AT_KV);
        tma_load_2d(x.sKV + i * AT_KV, x.tmKV, 0, (x.h * NMT + i) * 24, x.full + 8 * i);
      }
    }
  }
  if (x.w4 < 2) {
    const int g = x.lane >> 2, c = x.lane & 3;
    float* dst = g_kvpart + (size_t)(x.h * NMT + x.rb * 4 + x.wg) * 480;
    const int d0 = x.w4 * 16 + g;
#pragma unroll
    for (int b = 0; b < 3; b++) {
      if (d0 < 20) *reinterpret_cast<float2*>(dst + d0 * 24 + 8 * b + 2 * c) = make_float2(kv[4 * b], kv[4 * b + 1]);
      if (d0 + 8 < 20) *reinterpret_cast<float2*>(dst + (d0 + 8) * 24 + 8 * b + 2 * c) = make_float2(kv[4 * b + 2], kv[4 * b + 3]);
    }
    __threadfence();
    __syncwarp();
    if (x.lane == 0) asm volatile("red.release.gpu.global.add.u32 [%0], 1;" ::"l"(g_kvflag + x.h) : "memory");
  }
  __syncwarp();
}

__device__ __forceinline__ void kv_gather(const AttnCtx& x) {
  unsigned v, n = 0;
  do {
    asm volatile("ld.acquire.gpu.global.u32 %0, [%1];" : "=r"(v) : "l"(g_kvflag + x.h) : "memory");
    if (++n > (1u << 24)) __trap();
  } while (v < 32u);
#pragma unroll 1
  for (int i = 0; i < 3; i++) {
    const int pi = x.tid + 128 * i, d = pi / 12, e = (pi - d * 12) * 2;
    float sx = 0.f, sy = 0.f;
    if (d < 20) {
      const float* src = g_kvpart + (size_t)x.h * NMT * 480 + d * 24 + e;
#pragma unroll
      for (int m = 0; m < 16; m++) { float2 t = __ldcg(reinterpret_cast<const float2*>(src + m * 480)); sx += t.x; sy += t.y; }
    }
    *reinterpret_cast<uint32_t*>(x.sgen + 16 * AT_KV + (e >> 3) * 512 + d * 16 + (e & 7) * 2) = pack_bf16(sx, sy);
  }
  fence_proxy_async();
  mbar_arrive(x.kvbReady);
  __syncwarp();
}

template <int PASS>
__device__ __forceinline__ void pass_fast(const AttnCtx& x, const Frag6& q, float (&o)[12]) {
  float s[64];
  uint32_t p[32];
  PolyConst pc;
  pc.one = 0x3C003C00u; pc.c3 = 0x10FC10FCu;
  asm volatile("" : "+r"(pc.one), "+r"(pc.c3));
  uint32_t klo = desc_lo(x.sKV, CHB);
  uint32_t klo2 = desc_lo(x.sKV + 2 * CHB, 0);
  uint32_t vlo = desc_lo(x.sKV + HB, 128);
#pragma unroll 1
  for (int jt = 0; jt < 16; jt++) {
    if (PASS == 0) mbar_wait(x.full + 8 * jt, 0);
    WG_WAIT(0);
    fence_regs_u(p);
    WG_FENCE();
    wgmma_n128_rs_init(s, q.a0, q.a1, q.a2, q.a3, klo, KD_HI);
    wgmma_n128_rs_acc(s, q.b0, q.b1, 0u, 0u, klo2, KD_HI);
    WG_COMMIT();
    WG_WAIT(0);
    fence_regs(s);
#pragma unroll
    for (int b = 0; b < 16; b++) {
      if ((MUFU_MASK >> b) & 1) {
        p[2 * b] = pack_bf16(ex2f(s[4 * b]), ex2f(s[4 * b + 1]));
        p[2 * b + 1] = pack_bf16(ex2f(s[4 * b + 2]), ex2f(s[4 * b + 3]));
      } else {
        p[2 * b] = exp2_poly_pair(s[4 * b], s[4 * b + 1], pc);
        p[2 * b + 1] = exp2_poly_pair(s[4 * b + 2], s[4 * b + 3], pc);
      }
    }
    if (PASS == 0) {
      if (jt == 1) kv_partial(x);
      if (jt == 8 && x.wg == 0) kv_gather(x);
    }
    WG_FENCE();
    wgmma_n24_rs_tb(o, p[0], p[1], p[2], p[3], vlo, VD_HI, jt != 0);
#pragma unroll
    for (int kk = 1; kk < 8; kk++)
      wgmma_n24_rs_tb_acc(o, p[4 * kk], p[4 * kk + 1], p[4 * kk + 2], p[4 * kk + 3], vlo + kk * 16, VD_HI);
    WG_COMMIT();
    klo += AT_KV >> 4; klo2 += AT_KV >> 4; vlo += AT_KV >> 4;
  }
  WG_WAIT(0);
  fence_regs(o);
}

__device__ __noinline__ void pass_slow(const AttnCtx& x, const Frag6& q, float* ores, int pass) {
  float o[12];
  float m0 = -INFINITY, m1 = -INFINITY;
#pragma unroll
  for (int i = 0; i < 12; i++) o[i] = 0.f;
  fence_regs(o);
#pragma unroll 1
  for (int it = 0; it < 32; it++) {
    const int jt = it >> 1;
    if (pass == 0) {
      if (it == 4) kv_partial(x);
      if (it == 16 && x.wg == 0) kv_gather(x);
      mbar_wait(x.full + 8 * jt, 0);
    }
    float s2[32];
    uint32_t p2[16];
    const uint32_t kb = x.sKV + jt * AT_KV + (it & 1) * 1024;
    WG_FENCE();
    wgmma_n64_rs_init(s2, q.a0, q.a1, q.a2, q.a3, desc_lo(kb, CHB), KD_HI);
    wgmma_n64_rs_acc(s2, q.b0, q.b1, 0u, 0u, desc_lo(kb + 2 * CHB, 0), KD_HI);
    WG_COMMIT();
    WG_WAIT(0);
    fence_regs(s2);
    float x0 = m0, x1 = m1;
#pragma unroll
    for (int b = 0; b < 8; b++) {
      x0 = fmaxf(x0, fmaxf(s2[4 * b], s2[4 * b + 1]));
      x1 = fmaxf(x1, fmaxf(s2[4 * b + 2], s2[4 * b + 3]));
    }
    x0 = fmaxf(x0, __shfl_xor_sync(~0u, x0, 1)); x0 = fmaxf(x0, __shfl_xor_sync(~0u, x0, 2));
    x1 = fmaxf(x1, __shfl_xor_sync(~0u, x1, 1)); x1 = fmaxf(x1, __shfl_xor_sync(~0u, x1, 2));
    const float a0 = ex2f(m0 - x0), a1 = ex2f(m1 - x1);
    m0 = x0; m1 = x1;
#pragma unroll
    for (int b = 0; b < 3; b++) { o[4 * b] *= a0; o[4 * b + 1] *= a0; o[4 * b + 2] *= a1; o[4 * b + 3] *= a1; }
#pragma unroll
    for (int b = 0; b < 8; b++) {
      p2[2 * b] = pack_bf16(ex2f(s2[4 * b] - m0), ex2f(s2[4 * b + 1] - m0));
      p2[2 * b + 1] = pack_bf16(ex2f(s2[4 * b + 2] - m1), ex2f(s2[4 * b + 3] - m1));
    }
    const uint32_t vlo = desc_lo(kb + HB, 128);
    WG_FENCE();
#pragma unroll
    for (int kk = 0; kk < 4; kk++)
      wgmma_n24_rs_tb_acc(o, p2[4 * kk], p2[4 * kk + 1], p2[4 * kk + 2], p2[4 * kk + 3], vlo + kk * 16, VD_HI);
    WG_COMMIT();
    WG_WAIT(0);
    fence_regs(o);
    fence_regs_u(p2);
  }
#pragma unroll
  for (int i = 0; i < 12; i++) ores[i] = o[i];
}

__global__ void __launch_bounds__(512, 1)
attn_kernel(const __grid_constant__ CUtensorMap tmKV, const __grid_constant__ CUtensorMap tmKVA) {
  extern __shared__ uint8_t smem_raw[];
  const uint32_t sbase = (smem_u32(smem_raw) + 1023) & ~1023u;
  AttnCtx x;
  x.sgen = smem_raw + (sbase - smem_u32(smem_raw));
  x.sKV = sbase;
  const uint32_t sKVB = sbase + 16 * AT_KV, sBar = sKVB + 1536;
  x.full = sBar; x.kvaFull = sBar + 128; x.kvbReady = sBar + 136;
  x.sCnt = reinterpret_cast<unsigned*>(x.sgen + 16 * AT_KV + 1536 + 144);
  x.tmKV = &tmKV;
  const int tid = threadIdx.x, warp = __shfl_sync(~0u, tid >> 5, 0), lane = tid & 31;
  x.tid = tid; x.lane = lane; x.wg = warp >> 2; x.w4 = warp & 3;
  const int g = lane >> 2, c = lane & 3;
  const int h = blockIdx.x >> 2, rb = blockIdx.x & 3;
  x.h = h; x.rb = rb;
  if (tid == 0) {
    for (int i = 0; i < 16; i++) mbar_init(x.full + 8 * i, 1);
    mbar_init(x.kvaFull, 1);
    mbar_init(x.kvbReady, 128);
    *x.sCnt = 0;
    fence_barrier_init();
  }
  __syncthreads();
  if (tid == 480) {
    for (int i = 0; i < 2; i++) { mbar_expect_tx(x.full + 8 * i, AT_KV); tma_load_2d(x.sKV + i * AT_KV, &tmKV, 0, (h * NMT + i) * 24, x.full + 8 * i); }
    mbar_expect_tx(x.kvaFull, 4 * AT_KV);
    tma_load_2d(x.sKV + 11 * AT_KV, &tmKVA, 0, (h * NMT + rb * 4) * 24, x.kvaFull);
    for (int ii = 2; ii < 12; ii++) {
      const int i = ii < 11 ? ii : 15;
      mbar_expect_tx(x.full + 8 * i, AT_KV);
      tma_load_2d(x.sKV + i * AT_KV, &tmKV, 0, (h * NMT + i) * 24, x.full + 8 * i);
    }
  }
  __syncwarp();
  const int mt0 = rb * 4 + (x.wg >> 1), mt1 = mt0 + 2;
  const int row = (x.wg & 1) * 64 + x.w4 * 16 + g;
  const uint32_t foff = row * 16 + c * 4;
  Frag6 q = load_frag(g_QB + (size_t)(h * NMT + mt0) * HB + foff, c);
  float kmax2, qmax2;
  const float qn0 = g_nrmQ[h * 128 + mt0 * 8 + (x.wg & 1) * 4 + x.w4], qn1 = g_nrmQ[h * 128 + mt1 * 8 + (x.wg & 1) * 4 + x.w4];
  {
    float4 kv4 = *reinterpret_cast<const float4*>(g_nrmK + h * 128 + lane * 4);
    kmax2 = fmaxf(fmaxf(kv4.x, kv4.y), fmaxf(kv4.z, kv4.w));
    qmax2 = g_nrmQ[h * 128 + rb * 32 + lane];
#pragma unroll
    for (int o = 16; o >= 1; o >>= 1) {
      kmax2 = fmaxf(kmax2, __shfl_xor_sync(~0u, kmax2, o));
      qmax2 = fmaxf(qmax2, __shfl_xor_sync(~0u, qmax2, o));
    }
  }
  const bool fast = __all_sync(~0u, sqrtf(qmax2 * kmax2) * 1.02f <= FAST_M_LIMIT);
  uint32_t bias0 = 0, bias1 = 0;
  if (fast) {
    const uint32_t mb0 = (__float_as_uint(sqrtf(qn0 * kmax2) * 1.01f) + 0xFFFFu) >> 16;
    const uint32_t mb1 = (__float_as_uint(sqrtf(qn1 * kmax2) * 1.01f) + 0xFFFFu) >> 16;
    bias0 = c == 2 ? 0x3F803F80u : (mb0 | 0x3F808000u);
    bias1 = c == 2 ? 0x3F803F80u : (mb1 | 0x3F808000u);
  }
  if (c >= 2) { q.b0 = bias0; q.b1 = bias0; }
  float o[12];
  if (fast) pass_fast<0>(x, q, o);
  else pass_slow(x, q, o, 0);

  q = load_frag(g_QB + (size_t)(h * NMT + mt1) * HB + foff, c);
  if (c >= 2) { q.b0 = bias1; q.b1 = bias1; }
  const Frag6 pa = load_frag(g_PQA + (size_t)(h * NMT + mt0) * HB + foff, c);
  const Frag6 pb = load_frag(g_PQA + (size_t)(h * NMT + mt1) * HB + foff, c);
  const float g00 = g_gate[mt0 * 128 + row], g01 = g_gate[mt0 * 128 + row + 8];
  const float g10 = g_gate[mt1 * 128 + row], g11 = g_gate[mt1 * 128 + row + 8];
  uint8_t* dst0 = g_OC + (size_t)mt0 * 160 * CHB + row * 16;
  uint8_t* dst1 = dst0 + (size_t)2 * 160 * CHB;
  const int src2 = (lane & ~3) | 2;
  {
    const float l0 = __shfl_sync(~0u, o[8], src2), l1 = __shfl_sync(~0u, o[10], src2);
    store_o(o, (1.0f - g00) / l0, (1.0f - g01) / l1, dst0, 640 + h * 20, c);
  }
  {
    float oa[12], ob[12];
    const uint32_t blo = desc_lo(sKVB, 128);
    constexpr uint32_t bhi = desc_hi(512, 0);
    mbar_wait(x.kvbReady, 0);
    WG_FENCE();
    wgmma_n24_rs_tb_init(oa, pa.a0, pa.a1, pa.a2, pa.a3, blo, bhi);
    wgmma_n24_rs_tb_acc(oa, pa.b0, pa.b1, 0u, 0u, blo + 16, bhi);
    wgmma_n24_rs_tb_init(ob, pb.a0, pb.a1, pb.a2, pb.a3, blo, bhi);
    wgmma_n24_rs_tb_acc(ob, pb.b0, pb.b1, 0u, 0u, blo + 16, bhi);
    WG_COMMIT();
    WG_WAIT(0);
    fence_regs(oa);
    fence_regs(ob);
    const float d0 = __shfl_sync(~0u, oa[8], src2) + 1e-6f, d1 = __shfl_sync(~0u, oa[10], src2) + 1e-6f;
    store_o(oa, g00 / d0, g01 / d1, dst0, h * 20, c);
    const float e0 = __shfl_sync(~0u, ob[8], src2) + 1e-6f, e1 = __shfl_sync(~0u, ob[10], src2) + 1e-6f;
    store_o(ob, g10 / e0, g11 / e1, dst1, h * 20, c);
  }
  if (fast) pass_fast<1>(x, q, o);
  else pass_slow(x, q, o, 1);
  {
    const float l0 = __shfl_sync(~0u, o[8], src2), l1 = __shfl_sync(~0u, o[10], src2);
    store_o(o, (1.0f - g10) / l0, (1.0f - g11) / l1, dst1, 640 + h * 20, c);
  }
}

constexpr int G3_ST = 5;
constexpr int G3_STAGE = 16384 + 24576;
constexpr int G3_SMEM = G3_ST * G3_STAGE + 256 + 1024;

__global__ void __cluster_dims__(2, 1, 1) __launch_bounds__(288, 1)
gemm_out_kernel(const __grid_constant__ CUtensorMap tmOC, const __grid_constant__ CUtensorMap tmWoA,
                const __grid_constant__ CUtensorMap tmWoB, __nv_bfloat16* __restrict__ out) {
  extern __shared__ uint8_t smem_raw[];
  const uint32_t sbase = (smem_u32(smem_raw) + 1023) & ~1023u;
  uint8_t* sgen = smem_raw + (sbase - smem_u32(smem_raw));
  const uint32_t sBar = sbase + G3_ST * G3_STAGE;
  const uint32_t full = sBar, empty = sBar + 8 * G3_ST;
  const int tid = threadIdx.x, warp = __shfl_sync(~0u, tid >> 5, 0), lane = tid & 31;
  const int rank = blockIdx.x & 1, tile = blockIdx.x >> 1, mt = tile >> 2, nt = tile & 3;
  if (tid == 0) {
    for (int i = 0; i < G3_ST; i++) { mbar_init(full + 8 * i, 1); mbar_init(empty + 8 * i, 8); }
    fence_barrier_init();
  }
  if (blockIdx.x == 0 && tid < NH) g_kvflag[tid] = 0;
  __syncthreads();
  float acc[80];
  const int wg = warp >> 2, w4 = warp & 3;
  if (warp == 8) {
    if (lane == 0) {
      const CUtensorMap* tmW = rank ? &tmWoB : &tmWoA;
      for (int kb = 0; kb < 10; kb++) {
        const int s = kb % G3_ST;
        mbar_wait(empty + 8 * s, ((kb / G3_ST) & 1) ^ 1);
        mbar_expect_tx(full + 8 * s, G3_STAGE);
        tma_load_2d(sbase + s * G3_STAGE, &tmOC, 0, (mt * 160 + rank * 80 + kb * 8) * 4, full + 8 * s);
#pragma unroll
        for (int i = 0; i < 3; i++) tma_load_2d(sbase + s * G3_STAGE + 16384 + i * 8192, tmW, nt * 160 + 64 * i, kb * 64, full + 8 * s);
      }
    }
  } else {
    const uint32_t a_lo0 = desc_lo(sbase + wg * 1024, CHB), b_lo0 = desc_lo(sbase + 16384, 8192);
    constexpr uint32_t a_hi = desc_hi(128, 0), b_hi = desc_hi(1024, 1);
    for (int kb = 0; kb < 10; kb++) {
      const int s = kb % G3_ST;
      mbar_wait(full + 8 * s, (kb / G3_ST) & 1);
      const uint32_t alo = a_lo0 + s * (G3_STAGE >> 4), blo = b_lo0 + s * (G3_STAGE >> 4);
      WG_FENCE();
#pragma unroll
      for (int kk = 0; kk < 4; kk++) wgmma_n160_ss_tb(acc, alo + kk * 256, a_hi, blo + kk * 128, b_hi, (kb | kk) != 0);
      WG_COMMIT();
      if (kb > 0) {
        WG_WAIT(1);
        if (lane == 0) mbar_arrive(empty + 8 * ((kb - 1) % G3_ST));
      }
    }
    WG_WAIT(0);
    fence_regs(acc);
  }
  asm volatile("barrier.cluster.arrive.release.aligned;\nbarrier.cluster.wait.acquire.aligned;" ::: "memory");
  if (warp < 8) {
    uint32_t dst = sbase + (uint32_t)tid * 16, rdst;
    asm volatile("mapa.shared::cluster.u32 %0, %1, %2;" : "=r"(rdst) : "r"(dst), "r"(rank ^ 1));
#pragma unroll
    for (int i = 0; i < 10; i++) {
      float a, b, cc, d;
      if (rank == 0) { a = acc[40 + 4 * i]; b = acc[41 + 4 * i]; cc = acc[42 + 4 * i]; d = acc[43 + 4 * i]; }
      else { a = acc[4 * i]; b = acc[4 * i + 1]; cc = acc[4 * i + 2]; d = acc[4 * i + 3]; }
      asm volatile("st.shared::cluster.v4.f32 [%0], {%1,%2,%3,%4};" ::"r"(rdst + i * 4096), "f"(a), "f"(b), "f"(cc), "f"(d) : "memory");
    }
  }
  asm volatile("barrier.cluster.arrive.release.aligned;\nbarrier.cluster.wait.acquire.aligned;" ::: "memory");
  if (warp < 8) {
    const int row = mt * 128 + wg * 64 + w4 * 16 + (lane >> 2);
    __nv_bfloat16* o0 = out + (size_t)row * DM + nt * 160 + rank * 80 + (lane & 3) * 2;
#pragma unroll
    for (int i = 0; i < 10; i++) {
      float4 r = *reinterpret_cast<const float4*>(sgen + tid * 16 + i * 4096);
      float a, b, cc, d;
      if (rank == 0) { a = acc[4 * i]; b = acc[4 * i + 1]; cc = acc[4 * i + 2]; d = acc[4 * i + 3]; }
      else { a = acc[40 + 4 * i]; b = acc[41 + 4 * i]; cc = acc[42 + 4 * i]; d = acc[43 + 4 * i]; }
      *reinterpret_cast<uint32_t*>(o0 + 8 * i) = pack_bf16(a + r.x, b + r.y);
      *reinterpret_cast<uint32_t*>(o0 + 8 * DM + 8 * i) = pack_bf16(cc + r.z, d + r.w);
    }
  }
}

typedef CUresult (*EncodeFn)(CUtensorMap*, CUtensorMapDataType, cuuint32_t, void*, const cuuint64_t*, const cuuint64_t*,
                             const cuuint32_t*, const cuuint32_t*, CUtensorMapInterleave, CUtensorMapSwizzle,
                             CUtensorMapL2promotion, CUtensorMapFloatOOBfill);

void make_map_2d(EncodeFn enc, CUtensorMap* tm, const void* p, uint64_t cols, uint64_t rows, uint32_t bc, uint32_t br, CUtensorMapSwizzle sw) {
  cuuint64_t dims[2] = {cols, rows};
  cuuint64_t strides[1] = {cols * 2};
  cuuint32_t box[2] = {bc, br};
  cuuint32_t es[2] = {1, 1};
  enc(tm, CU_TENSOR_MAP_DATA_TYPE_BFLOAT16, 2, const_cast<void*>(p), dims, strides, box, es, CU_TENSOR_MAP_INTERLEAVE_NONE, sw,
      CU_TENSOR_MAP_L2_PROMOTION_L2_128B, CU_TENSOR_MAP_FLOAT_OOB_FILL_NONE);
}

}

extern "C" void kernel_launch(void* const* d_in, const int* in_sizes, int n_in, void* d_out, int out_size) {
  const __nv_bfloat16* x = (const __nv_bfloat16*)d_in[0];
  const void* wqkvA = d_in[1];
  const void* woA = d_in[2];
  const void* wqkvB = d_in[4];
  const void* woB = d_in[5];
  const __nv_bfloat16* gate_w = (const __nv_bfloat16*)d_in[6];

  static EncodeFn enc = nullptr;
  if (!enc) {
    void* fn = nullptr;
    cudaDriverEntryPointQueryResult st;
    cudaGetDriverEntryPoint("cuTensorMapEncodeTiled", &fn, cudaEnableDefault, &st);
    enc = (EncodeFn)fn;
    cudaFuncSetAttribute(gemm_qkv_kernel, cudaFuncAttributeMaxDynamicSharedMemorySize, G1_SMEM);
    cudaFuncSetAttribute(attn_kernel, cudaFuncAttributeMaxDynamicSharedMemorySize, AT_SMEM);
    cudaFuncSetAttribute(gemm_out_kernel, cudaFuncAttributeMaxDynamicSharedMemorySize, G3_SMEM);
  }
  static void *pKVB = nullptr, *pKVA = nullptr, *pOC = nullptr;
  if (!pKVB) { cudaGetSymbolAddress(&pKVB, g_KVB); cudaGetSymbolAddress(&pKVA, g_KVA); cudaGetSymbolAddress(&pOC, g_OC); }
  CUtensorMap tmX, tmWA, tmWB, tmWoA, tmWoB, tmKV, tmKVA, tmOC;
  make_map_2d(enc, &tmX, x, 640, 2048, 64, 128, CU_TENSOR_MAP_SWIZZLE_128B);
  make_map_2d(enc, &tmWA, wqkvA, 1920, 640, 64, 32, CU_TENSOR_MAP_SWIZZLE_128B);
  make_map_2d(enc, &tmWB, wqkvB, 1920, 640, 64, 32, CU_TENSOR_MAP_SWIZZLE_128B);
  make_map_2d(enc, &tmWoA, woA, 640, 640, 64, 64, CU_TENSOR_MAP_SWIZZLE_128B);
  make_map_2d(enc, &tmWoB, woB, 640, 640, 64, 64, CU_TENSOR_MAP_SWIZZLE_128B);
  make_map_2d(enc, &tmKV, pKVB, 256, NH * NMT * 24, 256, 24, CU_TENSOR_MAP_SWIZZLE_NONE);
  make_map_2d(enc, &tmKVA, pKVA, 256, NH * NMT * 24, 256, 96, CU_TENSOR_MAP_SWIZZLE_NONE);
  make_map_2d(enc, &tmOC, pOC, 256, NMT * 160 * 4, 256, 32, CU_TENSOR_MAP_SWIZZLE_NONE);

  cudaStream_t st = cudaStreamPerThread;
  const int stages = 7;
  if (stages & 1) gemm_qkv_kernel<<<128, 512, G1_SMEM, st>>>(tmX, tmWA, tmWB, x, gate_w);
  if (stages & 2) attn_kernel<<<128, 512, AT_SMEM, st>>>(tmKV, tmKVA);
  if (stages & 4) gemm_out_kernel<<<128, 288, G3_SMEM, st>>>(tmOC, tmWoA, tmWoB, (__nv_bfloat16*)d_out);
}
```

```cpp
#include <cuda_runtime.h>
#include <cuda_bf16.h>
#include <cuda.h>
#include <stdint.h>

#define USE_PDL 1

namespace {

constexpr int SEQ = 2048, DM = 640, NH = 32, NMT = 16;
constexpr int HB = 6144;
constexpr int CHB = 2048;
constexpr float QSCALE = 0.22360679774997896f * 1.4426950408889634f;

constexpr uint32_t MUFU_MASK = 0x4949u | 0x0000u;
constexpr float FAST_M_LIMIT = 60.0f;
#define POLY_FINE 0xBDF9u

__device__ __align__(1024) uint8_t g_QP[NH * NMT * 2 * HB];
__device__ __align__(1024) uint8_t g_KVB[NH * NMT * 2 * HB];
__device__ __align__(1024) uint8_t g_KVA[NH * NMT * 2 * HB];
__device__ __align__(1024) uint8_t g_OC[NMT * 160 * CHB];
__device__ float g_nrmQ[NH * 128];
__device__ float g_nrmK[NH * 128];
__device__ float g_gate[SEQ];
__device__ __align__(16) float g_kvpart[NH * 20 * 24];
__device__ unsigned g_kvflag[NH];

#define TS(k, slot, who)
__device__ __forceinline__ uint32_t smem_u32(const void* p) { return (uint32_t)__cvta_generic_to_shared(p); }
__device__ __forceinline__ void mbar_init(uint32_t bar, uint32_t cnt) {
  asm volatile("mbarrier.init.shared::cta.b64 [%0], %1;" ::"r"(bar), "r"(cnt) : "memory");
}
__device__ __forceinline__ void mbar_expect_tx(uint32_t bar, uint32_t bytes) {
  asm volatile("mbarrier.arrive.expect_tx.shared::cta.b64 _, [%0], %1;" ::"r"(bar), "r"(bytes) : "memory");
}
__device__ __forceinline__ void mbar_arrive(uint32_t bar) {
  asm volatile("mbarrier.arrive.shared::cta.b64 _, [%0];" ::"r"(bar) : "memory");
}
__device__ __forceinline__ void mbar_wait(uint32_t bar, uint32_t parity) {
  asm volatile(
      "{\n.reg .pred p;\n.reg .u32 n;\nmov.u32 n, 0;\n"
      "MW_LOOP:\nmbarrier.try_wait.parity.shared::cta.b64 p, [%0], %1;\n@p bra MW_DONE;\n"
      "add.u32 n, n, 1;\nsetp.lt.u32 p, n, 4194304;\n@p bra MW_LOOP;\ntrap;\nMW_DONE:\n}\n" ::"r"(bar), "r"(parity)
      : "memory");
}
__device__ __forceinline__ void mbar_spin(uint32_t bar, uint32_t parity) {
  asm volatile(
      "{\n.reg .pred p;\n.reg .u32 n;\nmov.u32 n, 0;\n"
      "MS_LOOP:\nmbarrier.test_wait.parity.shared::cta.b64 p, [%0], %1;\n@p bra MS_DONE;\n"
      "add.u32 n, n, 1;\nsetp.lt.u32 p, n, 268435456;\n@p bra MS_LOOP;\ntrap;\nMS_DONE:\n}\n" ::"r"(bar), "r"(parity)
      : "memory");
}
#define PWAIT mbar_wait
#define CWAIT mbar_wait
__device__ __forceinline__ void fence_barrier_init() { asm volatile("fence.mbarrier_init.release.cluster;" ::: "memory"); }
__device__ __forceinline__ void fence_proxy_async() { asm volatile("fence.proxy.async;" ::: "memory"); }
__device__ __forceinline__ void bulk_load(uint32_t dst, const void* src, uint32_t bytes, uint32_t bar) {
  asm volatile("cp.async.bulk.shared::cluster.global.mbarrier::complete_tx::bytes [%0], [%1], %2, [%3];"
               ::"r"(dst), "l"(src), "r"(bytes), "r"(bar) : "memory");
}
__device__ __forceinline__ void tma_load_2d(uint32_t dst, const CUtensorMap* tm, int c0, int c1, uint32_t bar) {
  asm volatile("cp.async.bulk.tensor.2d.shared::cluster.global.mbarrier::complete_tx::bytes [%0], [%1, {%3, %4}], [%2];"
               ::"r"(dst), "l"(tm), "r"(bar), "r"(c0), "r"(c1) : "memory");
}
__device__ __forceinline__ void tma_load_3d(uint32_t dst, const CUtensorMap* tm, int c0, int c1, int c2, uint32_t bar) {
  asm volatile("cp.async.bulk.tensor.3d.shared::cluster.global.mbarrier::complete_tx::bytes [%0], [%1, {%3, %4, %5}], [%2];"
               ::"r"(dst), "l"(tm), "r"(bar), "r"(c0), "r"(c1), "r"(c2) : "memory");
}
__device__ __forceinline__ void tma_load_3d_mc(uint32_t dst, const CUtensorMap* tm, int c0, int c1, int c2, uint32_t bar, uint16_t mask) {
  asm volatile("cp.async.bulk.tensor.3d.shared::cluster.global.mbarrier::complete_tx::bytes.multicast::cluster [%0], [%1, {%3, %4, %5}], [%2], %6;"
               ::"r"(dst), "l"(tm), "r"(bar), "r"(c0), "r"(c1), "r"(c2), "h"(mask) : "memory");
}
__device__ __forceinline__ void tma_store_2d(const CUtensorMap* tm, uint32_t src, int c0, int c1) {
  asm volatile("cp.async.bulk.tensor.2d.global.shared::cta.bulk_group [%0, {%2, %3}], [%1];" ::"l"(tm), "r"(src), "r"(c0), "r"(c1) : "memory");
}
__device__ __forceinline__ uint32_t mapa(uint32_t addr, uint32_t rank) {
  uint32_t r;
  asm volatile("mapa.shared::cluster.u32 %0, %1, %2;" : "=r"(r) : "r"(addr), "r"(rank));
  return r;
}
__device__ __forceinline__ void mbar_arrive_remote(uint32_t cluster_addr) {
  asm volatile("mbarrier.arrive.shared::cluster.b64 _, [%0];" ::"r"(cluster_addr) : "memory");
}
__device__ __forceinline__ void cluster_arrive() { asm volatile("barrier.cluster.arrive.release.aligned;" ::: "memory"); }
__device__ __forceinline__ void cluster_wait() { asm volatile("barrier.cluster.wait.acquire.aligned;" ::: "memory"); }
__device__ __forceinline__ void pdl_wait() { asm volatile("griddepcontrol.wait;" ::: "memory"); }
__device__ __forceinline__ void pdl_launch() { asm volatile("griddepcontrol.launch_dependents;" ::: "memory"); }
__device__ __forceinline__ void prefetch_l1(const void* p) { asm volatile("prefetch.global.L1 [%0];" ::"l"(p)); }
__device__ __forceinline__ void prefetch_tmap(const CUtensorMap* tm) {
  asm volatile("prefetch.tensormap [%0];" ::"l"(tm) : "memory");
}
__device__ __forceinline__ uint32_t desc_lo(uint32_t saddr, uint32_t lbo) { return ((saddr & 0x3FFFF) >> 4) | ((lbo >> 4) << 16); }
__host__ __device__ constexpr uint32_t desc_hi(uint32_t sbo, uint32_t swz) { return (sbo >> 4) | (swz << 30); }
#define WG_FENCE() asm volatile("wgmma.fence.sync.aligned;" ::: "memory")
#define WG_COMMIT() asm volatile("wgmma.commit_group.sync.aligned;" ::: "memory")
#define WG_WAIT(n) asm volatile("wgmma.wait_group.sync.aligned %0;" ::"n"(n) : "memory")
template <int N>
__device__ __forceinline__ void fence_regs(float (&d)[N]) {
#pragma unroll
  for (int i = 0; i < N; i++) asm volatile("" : "+f"(d[i])::"memory");
}
template <int N>
__device__ __forceinline__ void fence_regs_u(uint32_t (&d)[N]) {
#pragma unroll
  for (int i = 0; i < N; i++) asm volatile("" : "+r"(d[i])::"memory");
}
__device__ __forceinline__ uint32_t pack_bf16(float lo, float hi) {
  uint32_t r;
  asm("cvt.rn.bf16x2.f32 %0, %1, %2;" : "=r"(r) : "f"(hi), "f"(lo));
  return r;
}
__device__ __forceinline__ float ex2f(float x) {
  float r;
  asm("ex2.approx.ftz.f32 %0, %1;" : "=f"(r) : "f"(x));
  return r;
}
__device__ __forceinline__ float bf_lo(uint32_t v) { return __uint_as_float(v << 16); }
__device__ __forceinline__ float bf_hi(uint32_t v) { return __uint_as_float(v & 0xFFFF0000u); }
__device__ __forceinline__ uint32_t hfma2(uint32_t a, uint32_t b, uint32_t c) {
  uint32_t r;
  asm("fma.rn.f16x2 %0, %1, %2, %3;" : "=r"(r) : "r"(a), "r"(b), "r"(c));
  return r;
}

__device__ __forceinline__ void wgmma_n64_ss_tb_acc(float (&d)[32], uint32_t alo, uint32_t ahi, uint32_t blo, uint32_t bhi) {
  asm volatile("{\n.reg .pred p;\n.reg .b64 da, db;\nmov.b64 da, {%32, %33};\nmov.b64 db, {%34, %35};\nsetp.eq.b32 p, 0, 0;\n"
  "wgmma.mma_async.sync.aligned.m64n64k16.f32.bf16.bf16 {%0,%1,%2,%3,%4,%5,%6,%7,%8,%9,%10,%11,%12,%13,%14,%15,%16,%17,%18,%19,%20,%21,%22,%23,%24,%25,%26,%27,%28,%29,%30,%31}, da, db, p, 1, 1, 0, 1;\n}\n"
   : "+f"(d[0]),"+f"(d[1]),"+f"(d[2]),"+f"(d[3]),"+f"(d[4]),"+f"(d[5]),"+f"(d[6]),"+f"(d[7]),"+f"(d[8]),"+f"(d[9]),"+f"(d[10]),"+f"(d[11]),"+f"(d[12]),"+f"(d[13]),"+f"(d[14]),"+f"(d[15]),"+f"(d[16]),"+f"(d[17]),"+f"(d[18]),"+f"(d[19]),"+f"(d[20]),"+f"(d[21]),"+f"(d[22]),"+f"(d[23]),"+f"(d[24]),"+f"(d[25]),"+f"(d[26]),"+f"(d[27]),"+f"(d[28]),"+f"(d[29]),"+f"(d[30]),"+f"(d[31])
   : "r"(alo),"r"(ahi),"r"(blo),"r"(bhi));
}
__device__ __forceinline__ void wgmma_n64_ss_tb_init(float (&d)[32], uint32_t alo, uint32_t ahi, uint32_t blo, uint32_t bhi) {
  asm volatile("{\n.reg .pred p;\n.reg .b64 da, db;\nmov.b64 da, {%32, %33};\nmov.b64 db, {%34, %35};\nsetp.ne.b32 p, 0, 0;\n"
  "wgmma.mma_async.sync.aligned.m64n64k16.f32.bf16.bf16 {%0,%1,%2,%3,%4,%5,%6,%7,%8,%9,%10,%11,%12,%13,%14,%15,%16,%17,%18,%19,%20,%21,%22,%23,%24,%25,%26,%27,%28,%29,%30,%31}, da, db, p, 1, 1, 0, 1;\n}\n"
   : "=f"(d[0]),"=f"(d[1]),"=f"(d[2]),"=f"(d[3]),"=f"(d[4]),"=f"(d[5]),"=f"(d[6]),"=f"(d[7]),"=f"(d[8]),"=f"(d[9]),"=f"(d[10]),"=f"(d[11]),"=f"(d[12]),"=f"(d[13]),"=f"(d[14]),"=f"(d[15]),"=f"(d[16]),"=f"(d[17]),"=f"(d[18]),"=f"(d[19]),"=f"(d[20]),"=f"(d[21]),"=f"(d[22]),"=f"(d[23]),"=f"(d[24]),"=f"(d[25]),"=f"(d[26]),"=f"(d[27]),"=f"(d[28]),"=f"(d[29]),"=f"(d[30]),"=f"(d[31])
   : "r"(alo),"r"(ahi),"r"(blo),"r"(bhi));
}
__device__ __forceinline__ void wgmma_n96_ss_tb_acc(float (&d)[48], uint32_t alo, uint32_t ahi, uint32_t blo, uint32_t bhi) {
  asm volatile("{\n.reg .pred p;\n.reg .b64 da, db;\nmov.b64 da, {%48, %49};\nmov.b64 db, {%50, %51};\nsetp.eq.b32 p, 0, 0;\n"
  "wgmma.mma_async.sync.aligned.m64n96k16.f32.bf16.bf16 {%0,%1,%2,%3,%4,%5,%6,%7,%8,%9,%10,%11,%12,%13,%14,%15,%16,%17,%18,%19,%20,%21,%22,%23,%24,%25,%26,%27,%28,%29,%30,%31,%32,%33,%34,%35,%36,%37,%38,%39,%40,%41,%42,%43,%44,%45,%46,%47}, da, db, p, 1, 1, 0, 1;\n}\n"
   : "+f"(d[0]),"+f"(d[1]),"+f"(d[2]),"+f"(d[3]),"+f"(d[4]),"+f"(d[5]),"+f"(d[6]),"+f"(d[7]),"+f"(d[8]),"+f"(d[9]),"+f"(d[10]),"+f"(d[11]),"+f"(d[12]),"+f"(d[13]),"+f"(d[14]),"+f"(d[15]),"+f"(d[16]),"+f"(d[17]),"+f"(d[18]),"+f"(d[19]),"+f"(d[20]),"+f"(d[21]),"+f"(d[22]),"+f"(d[23]),"+f"(d[24]),"+f"(d[25]),"+f"(d[26]),"+f"(d[27]),"+f"(d[28]),"+f"(d[29]),"+f"(d[30]),"+f"(d[31]),"+f"(d[32]),"+f"(d[33]),"+f"(d[34]),"+f"(d[35]),"+f"(d[36]),"+f"(d[37]),"+f"(d[38]),"+f"(d[39]),"+f"(d[40]),"+f"(d[41]),"+f"(d[42]),"+f"(d[43]),"+f"(d[44]),"+f"(d[45]),"+f"(d[46]),"+f"(d[47])
   : "r"(alo),"r"(ahi),"r"(blo),"r"(bhi));
}
__device__ __forceinline__ void wgmma_n96_ss_tb_init(float (&d)[48], uint32_t alo, uint32_t ahi, uint32_t blo, uint32_t bhi) {
  asm volatile("{\n.reg .pred p;\n.reg .b64 da, db;\nmov.b64 da, {%48, %49};\nmov.b64 db, {%50, %51};\nsetp.ne.b32 p, 0, 0;\n"
  "wgmma.mma_async.sync.aligned.m64n96k16.f32.bf16.bf16 {%0,%1,%2,%3,%4,%5,%6,%7,%8,%9,%10,%11,%12,%13,%14,%15,%16,%17,%18,%19,%20,%21,%22,%23,%24,%25,%26,%27,%28,%29,%30,%31,%32,%33,%34,%35,%36,%37,%38,%39,%40,%41,%42,%43,%44,%45,%46,%47}, da, db, p, 1, 1, 0, 1;\n}\n"
   : "=f"(d[0]),"=f"(d[1]),"=f"(d[2]),"=f"(d[3]),"=f"(d[4]),"=f"(d[5]),"=f"(d[6]),"=f"(d[7]),"=f"(d[8]),"=f"(d[9]),"=f"(d[10]),"=f"(d[11]),"=f"(d[12]),"=f"(d[13]),"=f"(d[14]),"=f"(d[15]),"=f"(d[16]),"=f"(d[17]),"=f"(d[18]),"=f"(d[19]),"=f"(d[20]),"=f"(d[21]),"=f"(d[22]),"=f"(d[23]),"=f"(d[24]),"=f"(d[25]),"=f"(d[26]),"=f"(d[27]),"=f"(d[28]),"=f"(d[29]),"=f"(d[30]),"=f"(d[31]),"=f"(d[32]),"=f"(d[33]),"=f"(d[34]),"=f"(d[35]),"=f"(d[36]),"=f"(d[37]),"=f"(d[38]),"=f"(d[39]),"=f"(d[40]),"=f"(d[41]),"=f"(d[42]),"=f"(d[43]),"=f"(d[44]),"=f"(d[45]),"=f"(d[46]),"=f"(d[47])
   : "r"(alo),"r"(ahi),"r"(blo),"r"(bhi));
}
__device__ __forceinline__ void wgmma_n80_ss_tb_acc(float (&d)[40], uint32_t alo, uint32_t ahi, uint32_t blo, uint32_t bhi) {
  asm volatile("{\n.reg .pred p;\n.reg .b64 da, db;\nmov.b64 da, {%40, %41};\nmov.b64 db, {%42, %43};\nsetp.eq.b32 p, 0, 0;\n"
  "wgmma.mma_async.sync.aligned.m64n80k16.f32.bf16.bf16 {%0,%1,%2,%3,%4,%5,%6,%7,%8,%9,%10,%11,%12,%13,%14,%15,%16,%17,%18,%19,%20,%21,%22,%23,%24,%25,%26,%27,%28,%29,%30,%31,%32,%33,%34,%35,%36,%37,%38,%39}, da, db, p, 1, 1, 0, 1;\n}\n"
   : "+f"(d[0]),"+f"(d[1]),"+f"(d[2]),"+f"(d[3]),"+f"(d[4]),"+f"(d[5]),"+f"(d[6]),"+f"(d[7]),"+f"(d[8]),"+f"(d[9]),"+f"(d[10]),"+f"(d[11]),"+f"(d[12]),"+f"(d[13]),"+f"(d[14]),"+f"(d[15]),"+f"(d[16]),"+f"(d[17]),"+f"(d[18]),"+f"(d[19]),"+f"(d[20]),"+f"(d[21]),"+f"(d[22]),"+f"(d[23]),"+f"(d[24]),"+f"(d[25]),"+f"(d[26]),"+f"(d[27]),"+f"(d[28]),"+f"(d[29]),"+f"(d[30]),"+f"(d[31]),"+f"(d[32]),"+f"(d[33]),"+f"(d[34]),"+f"(d[35]),"+f"(d[36]),"+f"(d[37]),"+f"(d[38]),"+f"(d[39])
   : "r"(alo),"r"(ahi),"r"(blo),"r"(bhi));
}
__device__ __forceinline__ void wgmma_n80_ss_tb_init(float (&d)[40], uint32_t alo, uint32_t ahi, uint32_t blo, uint32_t bhi) {
  asm volatile("{\n.reg .pred p;\n.reg .b64 da, db;\nmov.b64 da, {%40, %41};\nmov.b64 db, {%42, %43};\nsetp.ne.b32 p, 0, 0;\n"
  "wgmma.mma_async.sync.aligned.m64n80k16.f32.bf16.bf16 {%0,%1,%2,%3,%4,%5,%6,%7,%8,%9,%10,%11,%12,%13,%14,%15,%16,%17,%18,%19,%20,%21,%22,%23,%24,%25,%26,%27,%28,%29,%30,%31,%32,%33,%34,%35,%36,%37,%38,%39}, da, db, p, 1, 1, 0, 1;\n}\n"
   : "=f"(d[0]),"=f"(d[1]),"=f"(d[2]),"=f"(d[3]),"=f"(d[4]),"=f"(d[5]),"=f"(d[6]),"=f"(d[7]),"=f"(d[8]),"=f"(d[9]),"=f"(d[10]),"=f"(d[11]),"=f"(d[12]),"=f"(d[13]),"=f"(d[14]),"=f"(d[15]),"=f"(d[16]),"=f"(d[17]),"=f"(d[18]),"=f"(d[19]),"=f"(d[20]),"=f"(d[21]),"=f"(d[22]),"=f"(d[23]),"=f"(d[24]),"=f"(d[25]),"=f"(d[26]),"=f"(d[27]),"=f"(d[28]),"=f"(d[29]),"=f"(d[30]),"=f"(d[31]),"=f"(d[32]),"=f"(d[33]),"=f"(d[34]),"=f"(d[35]),"=f"(d[36]),"=f"(d[37]),"=f"(d[38]),"=f"(d[39])
   : "r"(alo),"r"(ahi),"r"(blo),"r"(bhi));
}
__device__ __forceinline__ void wgmma_n128_rs_init(float (&d)[64], uint32_t a0, uint32_t a1, uint32_t a2, uint32_t a3, uint32_t blo, uint32_t bhi) {
  asm volatile("{\n.reg .pred p;\n.reg .b64 da, db;\nmov.b64 db, {%68, %69};\nsetp.ne.b32 p, 0, 0;\n"
  "wgmma.mma_async.sync.aligned.m64n128k16.f32.bf16.bf16 {%0,%1,%2,%3,%4,%5,%6,%7,%8,%9,%10,%11,%12,%13,%14,%15,%16,%17,%18,%19,%20,%21,%22,%23,%24,%25,%26,%27,%28,%29,%30,%31,%32,%33,%34,%35,%36,%37,%38,%39,%40,%41,%42,%43,%44,%45,%46,%47,%48,%49,%50,%51,%52,%53,%54,%55,%56,%57,%58,%59,%60,%61,%62,%63}, {%64,%65,%66,%67}, db, p, 1, 1, 0;\n}\n"
   : "=f"(d[0]),"=f"(d[1]),"=f"(d[2]),"=f"(d[3]),"=f"(d[4]),"=f"(d[5]),"=f"(d[6]),"=f"(d[7]),"=f"(d[8]),"=f"(d[9]),"=f"(d[10]),"=f"(d[11]),"=f"(d[12]),"=f"(d[13]),"=f"(d[14]),"=f"(d[15]),"=f"(d[16]),"=f"(d[17]),"=f"(d[18]),"=f"(d[19]),"=f"(d[20]),"=f"(d[21]),"=f"(d[22]),"=f"(d[23]),"=f"(d[24]),"=f"(d[25]),"=f"(d[26]),"=f"(d[27]),"=f"(d[28]),"=f"(d[29]),"=f"(d[30]),"=f"(d[31]),"=f"(d[32]),"=f"(d[33]),"=f"(d[34]),"=f"(d[35]),"=f"(d[36]),"=f"(d[37]),"=f"(d[38]),"=f"(d[39]),"=f"(d[40]),"=f"(d[41]),"=f"(d[42]),"=f"(d[43]),"=f"(d[44]),"=f"(d[45]),"=f"(d[46]),"=f"(d[47]),"=f"(d[48]),"=f"(d[49]),"=f"(d[50]),"=f"(d[51]),"=f"(d[52]),"=f"(d[53]),"=f"(d[54]),"=f"(d[55]),"=f"(d[56]),"=f"(d[57]),"=f"(d[58]),"=f"(d[59]),"=f"(d[60]),"=f"(d[61]),"=f"(d[62]),"=f"(d[63])
   : "r"(a0),"r"(a1),"r"(a2),"r"(a3),"r"(blo),"r"(bhi));
}
__device__ __forceinline__ void wgmma_n128_rs_acc(float (&d)[64], uint32_t a0, uint32_t a1, uint32_t a2, uint32_t a3, uint32_t blo, uint32_t bhi) {
  asm volatile("{\n.reg .pred p;\n.reg .b64 da, db;\nmov.b64 db, {%68, %69};\nsetp.eq.b32 p, 0, 0;\n"
  "wgmma.mma_async.sync.aligned.m64n128k16.f32.bf16.bf16 {%0,%1,%2,%3,%4,%5,%6,%7,%8,%9,%10,%11,%12,%13,%14,%15,%16,%17,%18,%19,%20,%21,%22,%23,%24,%25,%26,%27,%28,%29,%30,%31,%32,%33,%34,%35,%36,%37,%38,%39,%40,%41,%42,%43,%44,%45,%46,%47,%48,%49,%50,%51,%52,%53,%54,%55,%56,%57,%58,%59,%60,%61,%62,%63}, {%64,%65,%66,%67}, db, p, 1, 1, 0;\n}\n"
   : "+f"(d[0]),"+f"(d[1]),"+f"(d[2]),"+f"(d[3]),"+f"(d[4]),"+f"(d[5]),"+f"(d[6]),"+f"(d[7]),"+f"(d[8]),"+f"(d[9]),"+f"(d[10]),"+f"(d[11]),"+f"(d[12]),"+f"(d[13]),"+f"(d[14]),"+f"(d[15]),"+f"(d[16]),"+f"(d[17]),"+f"(d[18]),"+f"(d[19]),"+f"(d[20]),"+f"(d[21]),"+f"(d[22]),"+f"(d[23]),"+f"(d[24]),"+f"(d[25]),"+f"(d[26]),"+f"(d[27]),"+f"(d[28]),"+f"(d[29]),"+f"(d[30]),"+f"(d[31]),"+f"(d[32]),"+f"(d[33]),"+f"(d[34]),"+f"(d[35]),"+f"(d[36]),"+f"(d[37]),"+f"(d[38]),"+f"(d[39]),"+f"(d[40]),"+f"(d[41]),"+f"(d[42]),"+f"(d[43]),"+f"(d[44]),"+f"(d[45]),"+f"(d[46]),"+f"(d[47]),"+f"(d[48]),"+f"(d[49]),"+f"(d[50]),"+f"(d[51]),"+f"(d[52]),"+f"(d[53]),"+f"(d[54]),"+f"(d[55]),"+f"(d[56]),"+f"(d[57]),"+f"(d[58]),"+f"(d[59]),"+f"(d[60]),"+f"(d[61]),"+f"(d[62]),"+f"(d[63])
   : "r"(a0),"r"(a1),"r"(a2),"r"(a3),"r"(blo),"r"(bhi));
}
__device__ __forceinline__ void wgmma_n64_rs_init(float (&d)[32], uint32_t a0, uint32_t a1, uint32_t a2, uint32_t a3, uint32_t blo, uint32_t bhi) {
  asm volatile("{\n.reg .pred p;\n.reg .b64 da, db;\nmov.b64 db, {%36, %37};\nsetp.ne.b32 p, 0, 0;\n"
  "wgmma.mma_async.sync.aligned.m64n64k16.f32.bf16.bf16 {%0,%1,%2,%3,%4,%5,%6,%7,%8,%9,%10,%11,%12,%13,%14,%15,%16,%17,%18,%19,%20,%21,%22,%23,%24,%25,%26,%27,%28,%29,%30,%31}, {%32,%33,%34,%35}, db, p, 1, 1, 0;\n}\n"
   : "=f"(d[0]),"=f"(d[1]),"=f"(d[2]),"=f"(d[3]),"=f"(d[4]),"=f"(d[5]),"=f"(d[6]),"=f"(d[7]),"=f"(d[8]),"=f"(d[9]),"=f"(d[10]),"=f"(d[11]),"=f"(d[12]),"=f"(d[13]),"=f"(d[14]),"=f"(d[15]),"=f"(d[16]),"=f"(d[17]),"=f"(d[18]),"=f"(d[19]),"=f"(d[20]),"=f"(d[21]),"=f"(d[22]),"=f"(d[23]),"=f"(d[24]),"=f"(d[25]),"=f"(d[26]),"=f"(d[27]),"=f"(d[28]),"=f"(d[29]),"=f"(d[30]),"=f"(d[31])
   : "r"(a0),"r"(a1),"r"(a2),"r"(a3),"r"(blo),"r"(bhi));
}
__device__ __forceinline__ void wgmma_n64_rs_acc(float (&d)[32], uint32_t a0, uint32_t a1, uint32_t a2, uint32_t a3, uint32_t blo, uint32_t bhi) {
  asm volatile("{\n.reg .pred p;\n.reg .b64 da, db;\nmov.b64 db, {%36, %37};\nsetp.eq.b32 p, 0, 0;\n"
  "wgmma.mma_async.sync.aligned.m64n64k16.f32.bf16.bf16 {%0,%1,%2,%3,%4,%5,%6,%7,%8,%9,%10,%11,%12,%13,%14,%15,%16,%17,%18,%19,%20,%21,%22,%23,%24,%25,%26,%27,%28,%29,%30,%31}, {%32,%33,%34,%35}, db, p, 1, 1, 0;\n}\n"
   : "+f"(d[0]),"+f"(d[1]),"+f"(d[2]),"+f"(d[3]),"+f"(d[4]),"+f"(d[5]),"+f"(d[6]),"+f"(d[7]),"+f"(d[8]),"+f"(d[9]),"+f"(d[10]),"+f"(d[11]),"+f"(d[12]),"+f"(d[13]),"+f"(d[14]),"+f"(d[15]),"+f"(d[16]),"+f"(d[17]),"+f"(d[18]),"+f"(d[19]),"+f"(d[20]),"+f"(d[21]),"+f"(d[22]),"+f"(d[23]),"+f"(d[24]),"+f"(d[25]),"+f"(d[26]),"+f"(d[27]),"+f"(d[28]),"+f"(d[29]),"+f"(d[30]),"+f"(d[31])
   : "r"(a0),"r"(a1),"r"(a2),"r"(a3),"r"(blo),"r"(bhi));
}
__device__ __forceinline__ void wgmma_n24_rs_tb(float (&d)[12], uint32_t a0, uint32_t a1, uint32_t a2, uint32_t a3, uint32_t blo, uint32_t bhi, int sc) {
  asm volatile("{\n.reg .pred p;\n.reg .b64 da, db;\nmov.b64 db, {%16, %17};\nsetp.ne.b32 p, %18, 0;\n"
  "wgmma.mma_async.sync.aligned.m64n24k16.f32.bf16.bf16 {%0,%1,%2,%3,%4,%5,%6,%7,%8,%9,%10,%11}, {%12,%13,%14,%15}, db, p, 1, 1, 1;\n}\n"
   : "+f"(d[0]),"+f"(d[1]),"+f"(d[2]),"+f"(d[3]),"+f"(d[4]),"+f"(d[5]),"+f"(d[6]),"+f"(d[7]),"+f"(d[8]),"+f"(d[9]),"+f"(d[10]),"+f"(d[11])
   : "r"(a0),"r"(a1),"r"(a2),"r"(a3),"r"(blo),"r"(bhi),"r"(sc));
}
__device__ __forceinline__ void wgmma_n24_rs_tb_init(float (&d)[12], uint32_t a0, uint32_t a1, uint32_t a2, uint32_t a3, uint32_t blo, uint32_t bhi) {
  asm volatile("{\n.reg .pred p;\n.reg .b64 da, db;\nmov.b64 db, {%16, %17};\nsetp.ne.b32 p, 0, 0;\n"
  "wgmma.mma_async.sync.aligned.m64n24k16.f32.bf16.bf16 {%0,%1,%2,%3,%4,%5,%6,%7,%8,%9,%10,%11}, {%12,%13,%14,%15}, db, p, 1, 1, 1;\n}\n"
   : "=f"(d[0]),"=f"(d[1]),"=f"(d[2]),"=f"(d[3]),"=f"(d[4]),"=f"(d[5]),"=f"(d[6]),"=f"(d[7]),"=f"(d[8]),"=f"(d[9]),"=f"(d[10]),"=f"(d[11])
   : "r"(a0),"r"(a1),"r"(a2),"r"(a3),"r"(blo),"r"(bhi));
}
__device__ __forceinline__ void wgmma_n24_rs_tb_acc(float (&d)[12], uint32_t a0, uint32_t a1, uint32_t a2, uint32_t a3, uint32_t blo, uint32_t bhi) {
  asm volatile("{\n.reg .pred p;\n.reg .b64 da, db;\nmov.b64 db, {%16, %17};\nsetp.eq.b32 p, 0, 0;\n"
  "wgmma.mma_async.sync.aligned.m64n24k16.f32.bf16.bf16 {%0,%1,%2,%3,%4,%5,%6,%7,%8,%9,%10,%11}, {%12,%13,%14,%15}, db, p, 1, 1, 1;\n}\n"
   : "+f"(d[0]),"+f"(d[1]),"+f"(d[2]),"+f"(d[3]),"+f"(d[4]),"+f"(d[5]),"+f"(d[6]),"+f"(d[7]),"+f"(d[8]),"+f"(d[9]),"+f"(d[10]),"+f"(d[11])
   : "r"(a0),"r"(a1),"r"(a2),"r"(a3),"r"(blo),"r"(bhi));
}
__device__ __forceinline__ void wgmma_n24_ss_tatb_init(float (&d)[12], uint32_t alo, uint32_t ahi, uint32_t blo, uint32_t bhi) {
  asm volatile("{\n.reg .pred p;\n.reg .b64 da, db;\nmov.b64 da, {%12, %13};\nmov.b64 db, {%14, %15};\nsetp.ne.b32 p, 0, 0;\n"
  "wgmma.mma_async.sync.aligned.m64n24k16.f32.bf16.bf16 {%0,%1,%2,%3,%4,%5,%6,%7,%8,%9,%10,%11}, da, db, p, 1, 1, 1, 1;\n}\n"
   : "=f"(d[0]),"=f"(d[1]),"=f"(d[2]),"=f"(d[3]),"=f"(d[4]),"=f"(d[5]),"=f"(d[6]),"=f"(d[7]),"=f"(d[8]),"=f"(d[9]),"=f"(d[10]),"=f"(d[11])
   : "r"(alo),"r"(ahi),"r"(blo),"r"(bhi));
}
__device__ __forceinline__ void wgmma_n24_ss_tatb_acc(float (&d)[12], uint32_t alo, uint32_t ahi, uint32_t blo, uint32_t bhi) {
  asm volatile("{\n.reg .pred p;\n.reg .b64 da, db;\nmov.b64 da, {%12, %13};\nmov.b64 db, {%14, %15};\nsetp.eq.b32 p, 0, 0;\n"
  "wgmma.mma_async.sync.aligned.m64n24k16.f32.bf16.bf16 {%0,%1,%2,%3,%4,%5,%6,%7,%8,%9,%10,%11}, da, db, p, 1, 1, 1, 1;\n}\n"
   : "+f"(d[0]),"+f"(d[1]),"+f"(d[2]),"+f"(d[3]),"+f"(d[4]),"+f"(d[5]),"+f"(d[6]),"+f"(d[7]),"+f"(d[8]),"+f"(d[9]),"+f"(d[10]),"+f"(d[11])
   : "r"(alo),"r"(ahi),"r"(blo),"r"(bhi));
}

template <int N, int OFF>
__device__ __forceinline__ float (&subacc(float (&a)[80]))[N] { return reinterpret_cast<float(&)[N]>(a[OFF]); }
template <bool INIT>
__device__ __forceinline__ void mma_160(float (&acc)[80], uint32_t alo, uint32_t ahi, uint32_t blo, uint32_t bhi, uint32_t gs16) {
  if (INIT) { wgmma_n64_ss_tb_init(subacc<32, 0>(acc), alo, ahi, blo, bhi); wgmma_n96_ss_tb_init(subacc<48, 32>(acc), alo, ahi, blo + 2 * gs16, bhi); }
  else { wgmma_n64_ss_tb_acc(subacc<32, 0>(acc), alo, ahi, blo, bhi); wgmma_n96_ss_tb_acc(subacc<48, 32>(acc), alo, ahi, blo + 2 * gs16, bhi); }
}

constexpr int G1_A_BYTES = 10 * 16384;
#define EMPTY_CNT 16
constexpr int G1_BST = 6;
constexpr int G1_B_BYTES = 10240;
constexpr int G1_SMEM = G1_A_BYTES + G1_BST * G1_B_BYTES + 512 + 1024;

constexpr uint32_t HSTRIDE = NMT * 2 * HB;
__device__ __forceinline__ uint32_t pack_bf16_relu(float lo, float hi) {
  uint32_t r;
  asm("cvt.rn.relu.bf16x2.f32 %0, %1, %2;" : "=r"(r) : "f"(hi), "f"(lo));
  return r;
}
__device__ __forceinline__ uint32_t badd2(uint32_t a, uint32_t b) {
  uint32_t r;
  asm("add.rn.bf16x2 %0, %1, %2;" : "=r"(r) : "r"(a), "r"(b));
  return r;
}
__device__ __forceinline__ uint32_t bmax2(uint32_t a, uint32_t b) {
  uint32_t r;
  asm("max.bf16x2 %0, %1, %2;" : "=r"(r) : "r"(a), "r"(b));
  return r;
}
__device__ __forceinline__ uint32_t phi_pair(float a, float b) {
  const float ea = ex2f(fminf(a * 1.4426950408889634f, 0.f)) + 1e-6f, eb = ex2f(fminf(b * 1.4426950408889634f, 0.f)) + 1e-6f;
  return pack_bf16(fmaxf(a, 0.f) + ea, fmaxf(b, 0.f) + eb);
}

template <int KIND>
__device__ __forceinline__ void g1_epilogue(float (&acc)[80], uint8_t* base, int row, int lane,
                                            float* nrm  ) {
  const int c = lane & 3;
  uint8_t* ptr[5];
#pragma unroll
  for (int bb = 0; bb < 5; bb++) {
    int col = 8 * bb + 2 * c;
    int hl = col >= 20 ? 1 : 0;
    int dim = col - 20 * hl;
    ptr[bb] = base + (row * 16 + hl * HSTRIDE + (dim >> 3) * CHB + (dim & 7) * 2);
  }
  uint2 pad0 = make_uint2(0, 0), pad1 = make_uint2(0, 0);
  if (KIND == 2) {
#pragma unroll
    for (int i = 0; i < 2; i++) {
      int r = row + 8 * i;
      bool mufu = (MUFU_MASK >> (r >> 3)) & 1;
      uint32_t s20, s21, s23;
      if (mufu) { s20 = 0; s21 = 0x4280; s23 = 0; }
      else if (r & 1) { s20 = 0x4781; s21 = 0x4240; s23 = POLY_FINE; }
      else { s20 = 0x4780; s21 = 0x433F; s23 = POLY_FINE; }
      uint2 v = make_uint2(s20 | (s21 << 16), 0x3F80u | (s23 << 16));
      if (i == 0) pad0 = v; else pad1 = v;
    }
  } else if (KIND == 3) {
    pad0 = make_uint2(0x3F80u, 0); pad1 = pad0;
  }
  uint8_t* pptr = (c == 1 ? ptr[2] : ptr[4]) + 4;
#pragma unroll
  for (int p = 0; p < 4; p++) {
    float ne0 = 0.f, ne1 = 0.f, no0 = 0.f, no1 = 0.f, nm0, nm1;
#pragma unroll
    for (int bb = 0; bb < 5; bb++) {
      const int b = 5 * p + bb;
      float v0 = acc[4 * b], v1 = acc[4 * b + 1], v2 = acc[4 * b + 2], v3 = acc[4 * b + 3];
      uint32_t w0, w1;
      if (KIND == 0) { w0 = phi_pair(v0, v1); w1 = phi_pair(v2, v3); }
      else if (KIND == 1) { w0 = pack_bf16(v0 * QSCALE, v1 * QSCALE); w1 = pack_bf16(v2 * QSCALE, v3 * QSCALE); }
      else { w0 = pack_bf16(v0, v1); w1 = pack_bf16(v2, v3); }
      *reinterpret_cast<uint32_t*>(ptr[bb] + 2 * p * HSTRIDE) = w0;
      *reinterpret_cast<uint32_t*>(ptr[bb] + 2 * p * HSTRIDE + 128) = w1;
      if (KIND == 1 || KIND == 2) {
        if (bb < 2) { ne0 = fmaf(v0, v0, fmaf(v1, v1, ne0)); ne1 = fmaf(v2, v2, fmaf(v3, v3, ne1)); }
        else if (bb > 2) { no0 = fmaf(v0, v0, fmaf(v1, v1, no0)); no1 = fmaf(v2, v2, fmaf(v3, v3, no1)); }
        else { nm0 = fmaf(v0, v0, v1 * v1); nm1 = fmaf(v2, v2, v3 * v3); }
      }
    }
    if (KIND == 2 || KIND == 3) {
      if (c & 1) {
        *reinterpret_cast<uint2*>(pptr + 2 * p * HSTRIDE) = pad0;
        *reinterpret_cast<uint2*>(pptr + 2 * p * HSTRIDE + 128) = pad1;
      }
    }
    if (KIND == 1 || KIND == 2) {
      if (c < 2) { ne0 += nm0; ne1 += nm1; } else { no0 += nm0; no1 += nm1; }
      uint32_t r0 = pack_bf16(ne0, no0), r1 = pack_bf16(ne1, no1);
#pragma unroll
      for (int o = 1; o <= 2; o <<= 1) {
        r0 = badd2(r0, __shfl_xor_sync(~0u, r0, o));
        r1 = badd2(r1, __shfl_xor_sync(~0u, r1, o));
      }
      uint32_t m = bmax2(r0, r1);
#pragma unroll
      for (int o = 4; o <= 16; o <<= 1) m = bmax2(m, __shfl_xor_sync(~0u, m, o));
      constexpr float INFL = (KIND == 1 ? QSCALE * QSCALE : 1.0f) * 1.03f;
      if (lane == 0) { nrm[(2 * p) * 128] = bf_lo(m) * INFL; nrm[(2 * p + 1) * 128] = bf_hi(m) * INFL; }
    }
  }
}

__device__ __forceinline__ void g1_tile(int t, uint32_t a_lo0, uint32_t b_lo0, uint32_t fullA, uint32_t fullB, uint32_t emptyB,
                                        uint32_t order, int lane, int kind, uint8_t* base, int row, float* nrm, uint32_t emptyR) {
  float acc[80];
  constexpr uint32_t a_hi = desc_hi(1024, 1), b_hi = desc_hi(512, 2);
  int s = (t * 20) % G1_BST, ph = ((t * 20) / G1_BST) & 1, sp;
  {
    if (t == 0) mbar_wait(fullA, 0);
    mbar_wait(fullB + 8 * s, ph);
    TS(0, 1 + 4 * t, threadIdx.x >> 7);
    const uint32_t blo = b_lo0 + s * (G1_B_BYTES >> 4);
    WG_FENCE();
    mma_160<true>(acc, a_lo0, a_hi, blo, b_hi, 128);
    mma_160<false>(acc, a_lo0 + 2, a_hi, blo + 64, b_hi, 128);
    WG_COMMIT();
    sp = s;
    if (++s == G1_BST) { s = 0; ph ^= 1; }
  }
#pragma unroll 1
  for (int kb = 1; kb < 20; kb++) {
    if (t == 0 && !(kb & 1)) mbar_wait(fullA + 8 * (kb >> 1), 0);
    CWAIT(fullB + 8 * s, ph);
    if (kb == 19 && t < 2 && lane == 0) mbar_arrive(order + 8 * t);
    const uint32_t alo = a_lo0 + (kb >> 1) * 1024 + (kb & 1) * 4,
      blo = b_lo0 + s * (G1_B_BYTES >> 4);
    WG_FENCE();
    mma_160<false>(acc, alo, a_hi, blo, b_hi, 128);
    mma_160<false>(acc, alo + 2, a_hi, blo + 64, b_hi, 128);
    WG_COMMIT();
    WG_WAIT(1);
    if (lane == 0) { mbar_arrive(emptyB + 8 * sp); mbar_arrive_remote(emptyR + 8 * sp); }
    sp = s;
    if (++s == G1_BST) { s = 0; ph ^= 1; }
  }
  WG_WAIT(0);
  fence_regs(acc);
  if (lane == 0) { mbar_arrive(emptyB + 8 * sp); mbar_arrive_remote(emptyR + 8 * sp); }
  TS(0, 2 + 4 * t, threadIdx.x >> 7);
  if (kind == 0) g1_epilogue<0>(acc, base, row, lane, nrm);
  else if (kind == 1) g1_epilogue<1>(acc, base, row, lane, nrm);
  else if (kind == 2) g1_epilogue<2>(acc, base, row, lane, nrm);
  else g1_epilogue<3>(acc, base, row, lane, nrm);
  TS(0, 3 + 4 * t, threadIdx.x >> 7);
}

__global__ void __cluster_dims__(2, 1, 1) __launch_bounds__(640, 1)
gemm_qkv_kernel(const __grid_constant__ CUtensorMap tmX, const __grid_constant__ CUtensorMap tmWA,
                const __grid_constant__ CUtensorMap tmWB, const __nv_bfloat16* __restrict__ x,
                const __nv_bfloat16* __restrict__ gate_w) {
  extern __shared__ uint8_t smem_raw[];
  const uint32_t sbase = (smem_u32(smem_raw) + 1023) & ~1023u;
  const uint32_t sA = sbase, sB = sbase + G1_A_BYTES, sBar = sB + G1_BST * G1_B_BYTES;
  const uint32_t fullA = sBar, fullB = sBar + 80, emptyB = fullB + 8 * G1_BST, order = emptyB + 8 * G1_BST;
  const int tid = threadIdx.x, warp = __shfl_sync(~0u, tid >> 5, 0), lane = tid & 31;
  const int rank = blockIdx.x & 1, mt = (blockIdx.x >> 4) * 2 + rank, j = (blockIdx.x >> 1) & 7;
  const int branch = j >> 2, jj = j & 3;
  TS(0, 0, warp >> 2);
  if (tid == 512) {
    prefetch_tmap(&tmX); prefetch_tmap(branch ? &tmWB : &tmWA);
    for (int i = 0; i < 10; i++) mbar_init(fullA + 8 * i, 1);
    for (int i = 0; i < G1_BST; i++) { mbar_init(fullB + 8 * i, 1); mbar_init(emptyB + 8 * i, EMPTY_CNT); }
    mbar_init(order, 8); mbar_init(order + 8, 8);
    fence_barrier_init();
  }
  __syncwarp();
  cluster_arrive();
  cluster_wait();
  pdl_launch();
  if (warp >= 16) {
    asm volatile("setmaxnreg.dec.sync.aligned.u32 32;");
    if (lane == 0) {
      const CUtensorMap* tmW = branch ? &tmWB : &tmWA;
      for (int it = 0; it < 60; it++) {
        const int t = it / 20, kb = it - t * 20, s = it % G1_BST;
        if ((s % 3) != warp - 16) continue;
        if (t == 0 && !(kb & 1)) {
          mbar_expect_tx(fullA + 8 * (kb >> 1), 16384);
          tma_load_2d(sA + (kb >> 1) * 16384, &tmX, kb * 32, mt * 128, fullA + 8 * (kb >> 1));
        }
        const int type = 2 - t;
        const int jt = jj;
        PWAIT(emptyB + 8 * s, ((it / G1_BST) & 1) ^ 1);
        mbar_expect_tx(fullB + 8 * s, G1_B_BYTES);
        if ((it & 1) == rank) tma_load_3d_mc(sB + s * G1_B_BYTES, tmW, 0, kb * 32, type * 20 + jt * 5, fullB + 8 * s, 3);
      }
    }
    __syncwarp();
    cluster_arrive();
    cluster_wait();
  } else {
    asm volatile("setmaxnreg.inc.sync.aligned.u32 112;");
    const int grp = warp >> 3, wg = (warp >> 2) & 1, w4 = warp & 3;
    if (grp == 1) {
      const int w8 = warp - 8;
#pragma unroll
      for (int rr = 0; rr < 2; rr++) {
        const int row = mt * 128 + j * 16 + w8 * 2 + rr;
        const uint2* xp = reinterpret_cast<const uint2*>(x + (size_t)row * DM);
        const uint2* gp = reinterpret_cast<const uint2*>(gate_w);
        float s = 0.f;
#pragma unroll
        for (int i = 0; i < 5; i++) {
          uint2 a = __ldg(xp + lane + 32 * i), g = __ldg(gp + lane + 32 * i);
          s += bf_lo(a.x) * bf_lo(g.x) + bf_hi(a.x) * bf_hi(g.x) + bf_lo(a.y) * bf_lo(g.y) + bf_hi(a.y) * bf_hi(g.y);
        }
#pragma unroll
        for (int o = 16; o >= 1; o >>= 1) s += __shfl_xor_sync(~0u, s, o);
        if (lane == 0) g_gate[row] = 1.0f / (1.0f + __expf(-s));
      }
    }
    const uint32_t a_lo0 = desc_lo(sA + wg * 8192, 16), b_lo0 = desc_lo(sB, 2048);
    const uint32_t emptyR = mapa(emptyB, rank ^ 1);
#pragma unroll 1
    for (int t = grp; t < 3; t += 2) {
      if (t > 0) mbar_wait(order + 8 * (t - 1), 0);
      const int jt = jj;
      const int type = 2 - t;
      const int h0 = jt * 8;
      const int row = wg * 64 + w4 * 16 + (lane >> 2);
      const int grp16 = mt * 8 + wg * 4 + w4;
      int kind; uint8_t* base; float* nrm;
      const size_t boff = (size_t)(h0 * NMT + mt) * 2 * HB;
      if (type == 0) {
        base = g_QP + boff + (branch ? 0 : HB);
        kind = branch ? 1 : 0; nrm = g_nrmQ + h0 * 128 + grp16;
      } else {
        base = (branch ? g_KVB : g_KVA) + boff + (type == 2 ? HB : 0);
        kind = type == 2 ? 3 : (branch ? 2 : 0); nrm = g_nrmK + h0 * 128 + grp16;
      }
      g1_tile(t, a_lo0, b_lo0, fullA, fullB, emptyB, order, lane, kind, base, row, nrm, emptyR);
    }
    cluster_arrive();
    cluster_wait();
  }
}

constexpr int AT_KV = 2 * HB;
constexpr int AT_SMEM = 16 * AT_KV + 1536 + 256 + 1024;

struct PolyConst { uint32_t a2; };
__device__ __forceinline__ uint32_t exp2_poly_pair(float t0, float t1, const PolyConst& k) {
  uint32_t u = __float_as_uint(t1) * 65536u + __float_as_uint(t0);
  uint32_t z = u & 0x007F007Fu;
  uint32_t q = hfma2(k.a2, z, 0xB560B560u);
  q = hfma2(q, z, 0x00100010u);
  return u + q;
}

__device__ __forceinline__ void store_o(float (&o)[12], float sc0, float sc1, uint8_t* dst  , int colbase, int c) {
#pragma unroll
  for (int b = 0; b < 3; b++) {
    int dim = 8 * b + 2 * c;
    if (dim < 20) {
      int col = colbase + dim;
      uint8_t* q = dst + (col >> 3) * CHB + (col & 7) * 2;
      *reinterpret_cast<uint32_t*>(q) = pack_bf16(o[4 * b] * sc0, o[4 * b + 1] * sc0);
      *reinterpret_cast<uint32_t*>(q + 128) = pack_bf16(o[4 * b + 2] * sc1, o[4 * b + 3] * sc1);
    }
  }
}

struct Frag6 { uint32_t a0, a1, a2, a3, b0, b1; };
__device__ __forceinline__ Frag6 load_frag(const uint8_t* src  , int c) {
  Frag6 f;
  f.a0 = *reinterpret_cast<const uint32_t*>(src); f.a1 = *reinterpret_cast<const uint32_t*>(src + 128);
  f.a2 = *reinterpret_cast<const uint32_t*>(src + CHB); f.a3 = *reinterpret_cast<const uint32_t*>(src + CHB + 128);
  f.b0 = 0; f.b1 = 0;
  if (c < 2) { f.b0 = *reinterpret_cast<const uint32_t*>(src + 2 * CHB); f.b1 = *reinterpret_cast<const uint32_t*>(src + 2 * CHB + 128); }
  return f;
}

struct AttnCtx {
  uint32_t sKV, full, kvaFull, kvbReady;
  uint8_t* sgen;
  unsigned* sCnt;
  const CUtensorMap* tmKV;
  const uint8_t* pf;
  const float* pg;
  int h, rb, wg, w4, lane, tid;
};

constexpr uint32_t KD_HI = desc_hi(128, 0);
constexpr uint32_t VD_HI = desc_hi(CHB, 0);

__device__ __forceinline__ void kv_partial(const AttnCtx& x) {
  float kv[12];
  mbar_wait(x.kvaFull, 0);
  const uint32_t alo = desc_lo(x.sKV + (11 + x.wg) * AT_KV, 128), blo = alo + (HB >> 4);
  WG_FENCE();
  wgmma_n24_ss_tatb_init(kv, alo, VD_HI, blo, VD_HI);
#pragma unroll
  for (int kk = 1; kk < 8; kk++) wgmma_n24_ss_tatb_acc(kv, alo + kk * 16, VD_HI, blo + kk * 16, VD_HI);
  WG_COMMIT();
  WG_WAIT(0);
  fence_regs(kv);
  if (x.lane == 0) {
    unsigned old = atomicAdd(x.sCnt, 1u);
    if (old == 15) {
      fence_proxy_async();
      for (int i = 11; i < 15; i++) {
        mbar_expect_tx(x.full + 8 * i, AT_KV);
        tma_load_2d(x.sKV + i * AT_KV, x.tmKV, 0, (x.h * NMT + i) * 24, x.full + 8 * i);
      }
    }
  }
  if (x.w4 < 2) {
    const int g = x.lane >> 2, c = x.lane & 3;
    float* dst = g_kvpart + x.h * 480 + (x.w4 * 16 + g) * 24 + 2 * c;
    const int d0 = x.w4 * 16 + g;
#pragma unroll
    for (int b = 0; b < 3; b++) {
      if (d0 < 20) asm volatile("red.global.add.v2.f32 [%0], {%1, %2};" ::"l"(dst + 8 * b), "f"(kv[4 * b]), "f"(kv[4 * b + 1]) : "memory");
      if (d0 + 8 < 20) asm volatile("red.global.add.v2.f32 [%0], {%1, %2};" ::"l"(dst + 8 * 24 + 8 * b), "f"(kv[4 * b + 2]), "f"(kv[4 * b + 3]) : "memory");
    }
  }
  __syncwarp();
}
__device__ __forceinline__ void kv_publish(const AttnCtx& x) {
  if (x.w4 < 2) {
    __syncwarp();
    if (x.lane == 0) {
      __threadfence();
      asm volatile("red.release.gpu.global.add.u32 [%0], 1;" ::"l"(g_kvflag + x.h) : "memory");
    }
    __syncwarp();
  }
}

__device__ __forceinline__ void kv_gather(const AttnCtx& x) {
  unsigned v, n = 0;
  do {
    asm volatile("ld.acquire.gpu.global.u32 %0, [%1];" : "=r"(v) : "l"(g_kvflag + x.h) : "memory");
    if (++n > (1u << 24)) __trap();
  } while (v < 32u);
  float2 t[3];
#pragma unroll
  for (int i = 0; i < 3; i++) {
    const int pi = x.tid + 128 * i;
    t[i] = make_float2(0.f, 0.f);
    if (pi < 240) t[i] = __ldcg(reinterpret_cast<const float2*>(g_kvpart + x.h * 480 + 2 * pi));
  }
#pragma unroll
  for (int i = 0; i < 3; i++) {
    const int pi = x.tid + 128 * i, d = pi / 12, e = (pi - d * 12) * 2;
    *reinterpret_cast<uint32_t*>(x.sgen + 16 * AT_KV + (e >> 3) * 512 + d * 16 + (e & 7) * 2) = pack_bf16(t[i].x, t[i].y);
  }
  fence_proxy_async();
  mbar_arrive(x.kvbReady);
  __syncwarp();
}

template <int PASS>
__device__ __forceinline__ void pass_fast(const AttnCtx& x, const Frag6& q, float (&o)[12]) {
  PolyConst pc;
  pc.a2 = 0x793D793Du;
  asm volatile("" : "+r"(pc.a2));
  constexpr uint32_t T = AT_KV >> 4;
  uint32_t klo0 = desc_lo(x.sKV, CHB);
  uint32_t klo2 = desc_lo(x.sKV + 2 * CHB, 0);
  uint32_t vlo = desc_lo(x.sKV + HB, 128);
  uint32_t p[32];
#pragma unroll 1
  for (int jt = 0; jt < 16; jt++) {
    float s[64];
    if (PASS == 0) mbar_wait(x.full + 8 * jt, 0);
    if (PASS == 0) TS(1, 8 + jt, x.wg);
    WG_WAIT(0);
    fence_regs_u(p);
    if (PASS == 0) {
      if (jt == 3) kv_partial(x);
      if (jt == 5) kv_publish(x);
      if (jt == 11 && x.wg == 0) kv_gather(x);
      if (jt == 14) {
        const uint8_t* pq = x.pf;
        prefetch_l1(pq + HB); prefetch_l1(pq + HB + CHB); prefetch_l1(pq + HB + 2 * CHB);
        pq += 4 * HB;
        prefetch_l1(pq); prefetch_l1(pq + CHB); prefetch_l1(pq + 2 * CHB);
        prefetch_l1(pq + HB); prefetch_l1(pq + HB + CHB); prefetch_l1(pq + HB + 2 * CHB);
        prefetch_l1(x.pg); prefetch_l1(x.pg + 256);
      }
    }
    WG_FENCE();
    wgmma_n128_rs_init(s, q.a0, q.a1, q.a2, q.a3, klo0, KD_HI);
    wgmma_n128_rs_acc(s, q.b0, q.b1, 0u, 0u, klo2, KD_HI);
    WG_COMMIT();
    WG_WAIT(0);
    fence_regs(s);
#pragma unroll
    for (int qt = 0; qt < 4; qt++) {
#pragma unroll
      for (int b = 4 * qt; b < 4 * qt + 4; b++) {
        if ((MUFU_MASK >> b) & 1) {
          p[2 * b] = pack_bf16(ex2f(s[4 * b]), ex2f(s[4 * b + 1]));
          p[2 * b + 1] = pack_bf16(ex2f(s[4 * b + 2]), ex2f(s[4 * b + 3]));
        } else {
          p[2 * b] = exp2_poly_pair(s[4 * b], s[4 * b + 1], pc);
          p[2 * b + 1] = exp2_poly_pair(s[4 * b + 2], s[4 * b + 3], pc);
        }
      }
      WG_FENCE();
      if (qt == 0) wgmma_n24_rs_tb(o, p[0], p[1], p[2], p[3], vlo, VD_HI, jt != 0);
      else wgmma_n24_rs_tb_acc(o, p[8 * qt], p[8 * qt + 1], p[8 * qt + 2], p[8 * qt + 3], vlo + qt * 32, VD_HI);
      wgmma_n24_rs_tb_acc(o, p[8 * qt + 4], p[8 * qt + 5], p[8 * qt + 6], p[8 * qt + 7], vlo + qt * 32 + 16, VD_HI);
    }
    WG_COMMIT();
    klo0 += T; klo2 += T; vlo += T;
  }
  WG_WAIT(0);
  fence_regs(o);
}

__device__ __forceinline__ void pass_slow(const AttnCtx& x, const Frag6& q, float (&o)[12], int pass) {
  float m0 = -INFINITY, m1 = -INFINITY;
#pragma unroll
  for (int i = 0; i < 12; i++) o[i] = 0.f;
  fence_regs(o);
#pragma unroll 1
  for (int it = 0; it < 32; it++) {
    const int jt = it >> 1;
    if (pass == 0) {
      if (it == 4) kv_partial(x);
      if (it == 8) kv_publish(x);
      if (it == 16 && x.wg == 0) kv_gather(x);
      mbar_wait(x.full + 8 * jt, 0);
    }
    float s2[32];
    uint32_t p2[16];
    const uint32_t kb = x.sKV + jt * AT_KV + (it & 1) * 1024;
    WG_FENCE();
    wgmma_n64_rs_init(s2, q.a0, q.a1, q.a2, q.a3, desc_lo(kb, CHB), KD_HI);
    wgmma_n64_rs_acc(s2, q.b0, q.b1, 0u, 0u, desc_lo(kb + 2 * CHB, 0), KD_HI);
    WG_COMMIT();
    WG_WAIT(0);
    fence_regs(s2);
    float x0 = m0, x1 = m1;
#pragma unroll
    for (int b = 0; b < 8; b++) {
      x0 = fmaxf(x0, fmaxf(s2[4 * b], s2[4 * b + 1]));
      x1 = fmaxf(x1, fmaxf(s2[4 * b + 2], s2[4 * b + 3]));
    }
    x0 = fmaxf(x0, __shfl_xor_sync(~0u, x0, 1)); x0 = fmaxf(x0, __shfl_xor_sync(~0u, x0, 2));
    x1 = fmaxf(x1, __shfl_xor_sync(~0u, x1, 1)); x1 = fmaxf(x1, __shfl_xor_sync(~0u, x1, 2));
    const float a0 = ex2f(m0 - x0), a1 = ex2f(m1 - x1);
    m0 = x0; m1 = x1;
#pragma unroll
    for (int b = 0; b < 3; b++) { o[4 * b] *= a0; o[4 * b + 1] *= a0; o[4 * b + 2] *= a1; o[4 * b + 3] *= a1; }
#pragma unroll
    for (int b = 0; b < 8; b++) {
      p2[2 * b] = pack_bf16(ex2f(s2[4 * b] - m0), ex2f(s2[4 * b + 1] - m0));
      p2[2 * b + 1] = pack_bf16(ex2f(s2[4 * b + 2] - m1), ex2f(s2[4 * b + 3] - m1));
    }
    const uint32_t vlo = desc_lo(kb + HB, 128);
    WG_FENCE();
#pragma unroll
    for (int kk = 0; kk < 4; kk++)
      wgmma_n24_rs_tb_acc(o, p2[4 * kk], p2[4 * kk + 1], p2[4 * kk + 2], p2[4 * kk + 3], vlo + kk * 16, VD_HI);
    WG_COMMIT();
    WG_WAIT(0);
    fence_regs(o);
    fence_regs_u(p2);
  }
}

__global__ void __launch_bounds__(512, 1)
attn_kernel(const __grid_constant__ CUtensorMap tmKV, const __grid_constant__ CUtensorMap tmKVA) {
  extern __shared__ uint8_t smem_raw[];
  const uint32_t sbase = (smem_u32(smem_raw) + 1023) & ~1023u;
  AttnCtx x;
  x.sgen = smem_raw + (sbase - smem_u32(smem_raw));
  x.sKV = sbase;
  const uint32_t sKVB = sbase + 16 * AT_KV, sBar = sKVB + 1536;
  x.full = sBar; x.kvaFull = sBar + 128; x.kvbReady = sBar + 136;
  x.sCnt = reinterpret_cast<unsigned*>(x.sgen + 16 * AT_KV + 1536 + 144);
  x.tmKV = &tmKV;
  const int tid = threadIdx.x, warp = __shfl_sync(~0u, tid >> 5, 0), lane = tid & 31;
  x.tid = tid; x.lane = lane; x.wg = warp >> 2; x.w4 = warp & 3;
  const int g = lane >> 2, c = lane & 3;
  const int h = blockIdx.x >> 2, rb = blockIdx.x & 3;
  x.h = h; x.rb = rb;
  TS(1, 0, x.wg);
  if (tid == 0) {
    prefetch_tmap(&tmKV); prefetch_tmap(&tmKVA);
    for (int i = 0; i < 16; i++) mbar_init(x.full + 8 * i, 1);
    mbar_init(x.kvaFull, 1);
    mbar_init(x.kvbReady, 128);
    *x.sCnt = 0;
    fence_barrier_init();
  }
  __syncthreads();
  pdl_launch();
  pdl_wait();
  if (lane == 0 && warp < 13) {
    if (warp < 12) {
      const int i = warp < 11 ? warp : 15;
      mbar_expect_tx(x.full + 8 * i, AT_KV);
      tma_load_2d(x.sKV + i * AT_KV, &tmKV, 0, (h * NMT + i) * 24, x.full + 8 * i);
    } else {
      mbar_expect_tx(x.kvaFull, 4 * AT_KV);
      tma_load_2d(x.sKV + 11 * AT_KV, &tmKVA, 0, (h * NMT + rb * 4) * 24, x.kvaFull);
    }
  }
  __syncwarp();
  const int mt0 = rb * 4 + (x.wg >> 1), mt1 = mt0 + 2;
  const int row = (x.wg & 1) * 64 + x.w4 * 16 + g;
  const uint32_t foff = row * 16 + c * 4;
  x.pf = g_QP + (size_t)(h * NMT + mt0) * 2 * HB + foff + (lane & 1) * 128;
  x.pg = g_gate + mt0 * 128 + row;
  Frag6 q = load_frag(g_QP + (size_t)(h * NMT + mt0) * 2 * HB + foff, c);
  float kmax2, qmax2;
  const float qn0 = g_nrmQ[h * 128 + mt0 * 8 + (x.wg & 1) * 4 + x.w4], qn1 = g_nrmQ[h * 128 + mt1 * 8 + (x.wg & 1) * 4 + x.w4];
  {
    float4 kv4 = *reinterpret_cast<const float4*>(g_nrmK + h * 128 + lane * 4);
    kmax2 = fmaxf(fmaxf(kv4.x, kv4.y), fmaxf(kv4.z, kv4.w));
    qmax2 = g_nrmQ[h * 128 + rb * 32 + lane];
#pragma unroll
    for (int o = 16; o >= 1; o >>= 1) {
      kmax2 = fmaxf(kmax2, __shfl_xor_sync(~0u, kmax2, o));
      qmax2 = fmaxf(qmax2, __shfl_xor_sync(~0u, qmax2, o));
    }
  }
  const bool fast = __all_sync(~0u, sqrtf(qmax2 * kmax2) * 1.02f <= FAST_M_LIMIT);
  uint32_t bias0 = 0, bias1 = 0;
  if (fast) {
    const uint32_t mb0 = (__float_as_uint(sqrtf(qn0 * kmax2) * 1.01f) + 0xFFFFu) >> 16;
    const uint32_t mb1 = (__float_as_uint(sqrtf(qn1 * kmax2) * 1.01f) + 0xFFFFu) >> 16;
    bias0 = c == 2 ? 0x3F803F80u : (mb0 | 0x3F808000u);
    bias1 = c == 2 ? 0x3F803F80u : (mb1 | 0x3F808000u);
  }
  if (c >= 2) { q.b0 = bias0; q.b1 = bias0; }
  float o[12];
  TS(1, 1, x.wg);
  if (fast) pass_fast<0>(x, q, o);
  else pass_slow(x, q, o, 0);
  TS(1, 2, x.wg);

  q = load_frag(g_QP + (size_t)(h * NMT + mt1) * 2 * HB + foff, c);
  if (c >= 2) { q.b0 = bias1; q.b1 = bias1; }
  const Frag6 pa = load_frag(g_QP + (size_t)(h * NMT + mt0) * 2 * HB + HB + foff, c);
  const Frag6 pb = load_frag(g_QP + (size_t)(h * NMT + mt1) * 2 * HB + HB + foff, c);
  const float g00 = g_gate[mt0 * 128 + row], g01 = g_gate[mt0 * 128 + row + 8];
  const float g10 = g_gate[mt1 * 128 + row], g11 = g_gate[mt1 * 128 + row + 8];
  uint8_t* dst0 = g_OC + (size_t)mt0 * 160 * CHB + row * 16;
  uint8_t* dst1 = dst0 + (size_t)2 * 160 * CHB;
  const int src2 = (lane & ~3) | 2;
  {
    const float l0 = __shfl_sync(~0u, o[8], src2), l1 = __shfl_sync(~0u, o[10], src2);
    store_o(o, (1.0f - g00) / l0, (1.0f - g01) / l1, dst0, 640 + h * 20, c);
  }
  {
    float oa[12], ob[12];
    const uint32_t blo = desc_lo(sKVB, 128);
    constexpr uint32_t bhi = desc_hi(512, 0);
    mbar_wait(x.kvbReady, 0);
    WG_FENCE();
    wgmma_n24_rs_tb_init(oa, pa.a0, pa.a1, pa.a2, pa.a3, blo, bhi);
    wgmma_n24_rs_tb_acc(oa, pa.b0, pa.b1, 0u, 0u, blo + 16, bhi);
    wgmma_n24_rs_tb_init(ob, pb.a0, pb.a1, pb.a2, pb.a3, blo, bhi);
    wgmma_n24_rs_tb_acc(ob, pb.b0, pb.b1, 0u, 0u, blo + 16, bhi);
    WG_COMMIT();
    WG_WAIT(0);
    fence_regs(oa);
    fence_regs(ob);
    const float d0 = __shfl_sync(~0u, oa[8], src2) + 1e-6f, d1 = __shfl_sync(~0u, oa[10], src2) + 1e-6f;
    store_o(oa, g00 / d0, g01 / d1, dst0, h * 20, c);
    const float e0 = __shfl_sync(~0u, ob[8], src2) + 1e-6f, e1 = __shfl_sync(~0u, ob[10], src2) + 1e-6f;
    store_o(ob, g10 / e0, g11 / e1, dst1, h * 20, c);
  }
  TS(1, 3, x.wg);
  if (fast) pass_fast<1>(x, q, o);
  else pass_slow(x, q, o, 1);
  TS(1, 4, x.wg);
  {
    const float l0 = __shfl_sync(~0u, o[8], src2), l1 = __shfl_sync(~0u, o[10], src2);
    store_o(o, (1.0f - g10) / l0, (1.0f - g11) / l1, dst1, 640 + h * 20, c);
  }
  TS(1, 5, x.wg);
}

constexpr int G3_ST = 5;
constexpr int G3_STAGE = 16384 + 20480;
constexpr int G3_XCH = G3_ST * G3_STAGE;
constexpr int G3_SMEM = G3_XCH + 40960 + 256 + 1024;

__device__ __forceinline__ void g3_consumer(uint32_t sbase, uint8_t* sgen, uint32_t full, uint32_t empty, uint32_t xbar, int tid, int lane,
                                            int wg, int w4, int rank, int mt, int nt, const CUtensorMap* tmOut) {
  float acc[80];
  const uint32_t a_lo0 = desc_lo(sbase + wg * 1024, CHB), b_lo0 = desc_lo(sbase + 16384, 4096);
  constexpr uint32_t a_hi = desc_hi(128, 0), b_hi = desc_hi(512, 2);
  {
    mbar_wait(full, 0);
    TS(2, 1, wg);
    WG_FENCE();
    mma_160<true>(acc, a_lo0, a_hi, b_lo0, b_hi, 256);
#pragma unroll
    for (int kk = 1; kk < 4; kk++) mma_160<false>(acc, a_lo0 + kk * 256, a_hi, b_lo0 + kk * 64, b_hi, 256);
    WG_COMMIT();
  }
#pragma unroll 1
  for (int kb = 1; kb < 10; kb++) {
    const int s = kb % G3_ST;
    mbar_wait(full + 8 * s, (kb / G3_ST) & 1);
    const uint32_t alo = a_lo0 + s * (G3_STAGE >> 4), blo = b_lo0 + s * (G3_STAGE >> 4);
    WG_FENCE();
#pragma unroll
    for (int kk = 0; kk < 4; kk++) mma_160<false>(acc, alo + kk * 256, a_hi, blo + kk * 64, b_hi, 256);
    WG_COMMIT();
    WG_WAIT(1);
    if (lane == 0) mbar_arrive(empty + 8 * ((kb - 1) % G3_ST));
  }
  WG_WAIT(0);
  fence_regs(acc);
  TS(2, 2, wg);
  cluster_wait();
  {
    const uint32_t rdst = mapa(sbase + G3_XCH + (uint32_t)tid * 16, rank ^ 1), rbar = mapa(xbar, rank ^ 1);
#pragma unroll
    for (int i = 0; i < 10; i++) {
      float a, b, cc, d;
      if (rank == 0) { a = acc[40 + 4 * i]; b = acc[41 + 4 * i]; cc = acc[42 + 4 * i]; d = acc[43 + 4 * i]; }
      else { a = acc[4 * i]; b = acc[4 * i + 1]; cc = acc[4 * i + 2]; d = acc[4 * i + 3]; }
      asm volatile("st.async.weak.shared::cluster.mbarrier::complete_tx::bytes.v4.f32 [%0], {%1,%2,%3,%4}, [%5];"
                   ::"r"(rdst + i * 4096), "f"(a), "f"(b), "f"(cc), "f"(d), "r"(rbar) : "memory");
    }
  }
  TS(2, 3, wg);
  asm volatile("bar.sync 1, 256;" ::: "memory");
  mbar_wait(xbar, 0);
  TS(2, 4, wg);
  uint8_t* stg = sgen + wg * 10240 + (w4 * 16 + (lane >> 2)) * 160 + (lane & 3) * 4;
#pragma unroll
  for (int i = 0; i < 10; i++) {
    float4 r = *reinterpret_cast<const float4*>(sgen + G3_XCH + tid * 16 + i * 4096);
    float a, b, cc, d;
    if (rank == 0) { a = acc[4 * i]; b = acc[4 * i + 1]; cc = acc[4 * i + 2]; d = acc[4 * i + 3]; }
    else { a = acc[40 + 4 * i]; b = acc[41 + 4 * i]; cc = acc[42 + 4 * i]; d = acc[43 + 4 * i]; }
    *reinterpret_cast<uint32_t*>(stg + 16 * i) = pack_bf16(a + r.x, b + r.y);
    *reinterpret_cast<uint32_t*>(stg + 8 * 160 + 16 * i) = pack_bf16(cc + r.z, d + r.w);
  }
  asm volatile("fence.proxy.async.shared::cta;" ::: "memory");
  asm volatile("bar.sync %0, 128;" ::"r"(2 + wg) : "memory");
  if ((tid & 127) == 0) {
    tma_store_2d(tmOut, sbase + wg * 10240, nt * 160 + rank * 80, mt * 128 + wg * 64);
    asm volatile("cp.async.bulk.commit_group;" ::: "memory");
    asm volatile("cp.async.bulk.wait_group.read 0;" ::: "memory");
  }
  TS(2, 5, wg);
}

__global__ void __cluster_dims__(2, 1, 1) __launch_bounds__(320, 1)
gemm_out_kernel(const __grid_constant__ CUtensorMap tmOC, const __grid_constant__ CUtensorMap tmWoA,
                const __grid_constant__ CUtensorMap tmWoB, const __grid_constant__ CUtensorMap tmOut) {
  extern __shared__ uint8_t smem_raw[];
  const uint32_t sbase = (smem_u32(smem_raw) + 1023) & ~1023u;
  uint8_t* sgen = smem_raw + (sbase - smem_u32(smem_raw));
  const uint32_t sBar = sbase + G3_XCH + 40960;
  const uint32_t full = sBar, empty = sBar + 8 * G3_ST, xbar = empty + 8 * G3_ST;
  const int tid = threadIdx.x, warp = __shfl_sync(~0u, tid >> 5, 0), lane = tid & 31;
  const int rank = blockIdx.x & 1, tile = blockIdx.x >> 1, mt = tile >> 2, nt = tile & 3;
  TS(2, 0, warp >> 2);
  if (tid == 256) {
    prefetch_tmap(&tmOC); prefetch_tmap(rank ? &tmWoB : &tmWoA); prefetch_tmap(&tmOut);
    for (int i = 0; i < G3_ST; i++) { mbar_init(full + 8 * i, 2); mbar_init(empty + 8 * i, 8); }
    mbar_init(xbar, 1);
    fence_barrier_init();
    mbar_expect_tx(xbar, 40960);
  }
  __syncthreads();
  cluster_arrive();
  if (warp >= 8) {
    if (warp == 8) {
      pdl_wait();
      if (lane < 30) *reinterpret_cast<float4*>(g_kvpart + blockIdx.x * 120 + lane * 4) = make_float4(0.f, 0.f, 0.f, 0.f);
      if (blockIdx.x == 0) g_kvflag[lane] = 0;
    }
    if (lane == 0) {
      const CUtensorMap* tmW = rank ? &tmWoB : &tmWoA;
      for (int kb = 0; kb < 10; kb++) {
        const int s = kb % G3_ST;
        mbar_wait(empty + 8 * s, ((kb / G3_ST) & 1) ^ 1);
        if (warp == 8) {
          mbar_expect_tx(full + 8 * s, 16384);
          tma_load_2d(sbase + s * G3_STAGE, &tmOC, 0, (mt * 160 + rank * 80 + kb * 8) * 4, full + 8 * s);
        } else {
          mbar_expect_tx(full + 8 * s, 20480);
          tma_load_3d(sbase + s * G3_STAGE + 16384, tmW, 0, kb * 64, nt * 5, full + 8 * s);
        }
      }
    }
    __syncwarp();
    cluster_wait();
  } else {
    g3_consumer(sbase, sgen, full, empty, xbar, tid, lane, warp >> 2, warp & 3, rank, mt, nt, &tmOut);
  }
}

typedef CUresult (*EncodeFn)(CUtensorMap*, CUtensorMapDataType, cuuint32_t, void*, const cuuint64_t*, const cuuint64_t*,
                             const cuuint32_t*, const cuuint32_t*, CUtensorMapInterleave, CUtensorMapSwizzle,
                             CUtensorMapL2promotion, CUtensorMapFloatOOBfill);

void make_map_2d(EncodeFn enc, CUtensorMap* tm, const void* p, uint64_t cols, uint64_t rows, uint32_t bc, uint32_t br, CUtensorMapSwizzle sw) {
  cuuint64_t dims[2] = {cols, rows};
  cuuint64_t strides[1] = {cols * 2};
  cuuint32_t box[2] = {bc, br};
  cuuint32_t es[2] = {1, 1};
  enc(tm, CU_TENSOR_MAP_DATA_TYPE_BFLOAT16, 2, const_cast<void*>(p), dims, strides, box, es, CU_TENSOR_MAP_INTERLEAVE_NONE, sw,
      CU_TENSOR_MAP_L2_PROMOTION_L2_128B, CU_TENSOR_MAP_FLOAT_OOB_FILL_NONE);
}

void make_w_map(EncodeFn enc, CUtensorMap* tm, const void* w, int ncols, int krows) {
  cuuint64_t dims[3] = {32, 640, (cuuint64_t)(ncols / 32)};
  cuuint64_t strides[2] = {(cuuint64_t)ncols * 2, 64};
  cuuint32_t box[3] = {32, (cuuint32_t)krows, 5};
  cuuint32_t es[3] = {1, 1, 1};
  enc(tm, CU_TENSOR_MAP_DATA_TYPE_BFLOAT16, 3, const_cast<void*>(w), dims, strides, box, es, CU_TENSOR_MAP_INTERLEAVE_NONE,
      CU_TENSOR_MAP_SWIZZLE_64B, CU_TENSOR_MAP_L2_PROMOTION_L2_128B, CU_TENSOR_MAP_FLOAT_OOB_FILL_NONE);
}

}

extern "C" void kernel_launch(void* const* d_in, const int* in_sizes, int n_in, void* d_out, int out_size) {
  const __nv_bfloat16* x = (const __nv_bfloat16*)d_in[0];
  const void* wqkvA = d_in[1];
  const void* woA = d_in[2];
  const void* wqkvB = d_in[4];
  const void* woB = d_in[5];
  const __nv_bfloat16* gate_w = (const __nv_bfloat16*)d_in[6];

  static EncodeFn enc = nullptr;
  if (!enc) {
    void* fn = nullptr;
    cudaDriverEntryPointQueryResult st;
    cudaGetDriverEntryPoint("cuTensorMapEncodeTiled", &fn, cudaEnableDefault, &st);
    enc = (EncodeFn)fn;
    cudaFuncSetAttribute(gemm_qkv_kernel, cudaFuncAttributeMaxDynamicSharedMemorySize, G1_SMEM);
    cudaFuncSetAttribute(attn_kernel, cudaFuncAttributeMaxDynamicSharedMemorySize, AT_SMEM);
    cudaFuncSetAttribute(gemm_out_kernel, cudaFuncAttributeMaxDynamicSharedMemorySize, G3_SMEM);
  }
  static void *pKVB = nullptr, *pKVA = nullptr, *pOC = nullptr;
  if (!pKVB) { cudaGetSymbolAddress(&pKVB, g_KVB); cudaGetSymbolAddress(&pKVA, g_KVA); cudaGetSymbolAddress(&pOC, g_OC); }
  CUtensorMap tmX, tmWA, tmWB, tmWoA, tmWoB, tmKV, tmKVA, tmOC, tmOut;
  make_map_2d(enc, &tmOut, d_out, 640, 2048, 80, 64, CU_TENSOR_MAP_SWIZZLE_NONE);
  make_map_2d(enc, &tmX, x, 640, 2048, 64, 128, CU_TENSOR_MAP_SWIZZLE_128B);
  make_w_map(enc, &tmWA, wqkvA, 1920, 32);
  make_w_map(enc, &tmWB, wqkvB, 1920, 32);
  make_w_map(enc, &tmWoA, woA, 640, 64);
  make_w_map(enc, &tmWoB, woB, 640, 64);
  make_map_2d(enc, &tmKV, pKVB, 256, NH * NMT * 24, 256, 24, CU_TENSOR_MAP_SWIZZLE_NONE);
  make_map_2d(enc, &tmKVA, pKVA, 256, NH * NMT * 24, 256, 96, CU_TENSOR_MAP_SWIZZLE_NONE);
  make_map_2d(enc, &tmOC, pOC, 256, NMT * 160 * 4, 256, 32, CU_TENSOR_MAP_SWIZZLE_NONE);

  cudaStream_t st = cudaStreamPerThread;
  const int stages = 7;
  if (stages & 1) gemm_qkv_kernel<<<128, 640, G1_SMEM, st>>>(tmX, tmWA, tmWB, x, gate_w);
  cudaLaunchAttribute at[1];
  at[0].id = cudaLaunchAttributeProgrammaticStreamSerialization;
  at[0].val.programmaticStreamSerializationAllowed = 1;
  cudaLaunchConfig_t cfg = {};
  cfg.stream = st; cfg.attrs = at; cfg.numAttrs = USE_PDL;
  cfg.gridDim = dim3(128); cfg.blockDim = dim3(512); cfg.dynamicSmemBytes = AT_SMEM;
  if (stages & 2) cudaLaunchKernelEx(&cfg, attn_kernel, tmKV, tmKVA);
  cfg.blockDim = dim3(320); cfg.dynamicSmemBytes = G3_SMEM;
  if (stages & 4) cudaLaunchKernelEx(&cfg, gemm_out_kernel, tmOC, tmWoA, tmWoB, tmOut);
}
```

```cpp
#include <cuda_runtime.h>
#include <cuda_bf16.h>
#include <cuda.h>
#include <stdint.h>

namespace {

constexpr int SEQ = 2048, DM = 640, NH = 32, NMT = 16;
constexpr int HB = 6144;
constexpr int CHB = 2048;
constexpr float QSCALE = 0.22360679774997896f * 1.4426950408889634f;

constexpr uint32_t MUFU_MASK = 0x2525u;
constexpr float FAST_M_LIMIT = 40.0f;
#define POLY_FINE 0xBDF9u

__device__ __align__(1024) uint8_t g_QP[NH * NMT * 2 * HB];
__device__ __align__(1024) uint8_t g_KVB[NH * NMT * 2 * HB];
__device__ __align__(1024) uint8_t g_KVA[NH * NMT * 2 * HB];
__device__ __align__(1024) uint8_t g_OC[NMT * 160 * CHB];
__device__ float g_nrmQ[NH * 128];
__device__ float g_nrmK[NH * 128];
__device__ float g_gate[SEQ];
__device__ __align__(16) float g_kvpart[NH * 24 * 24];
__device__ unsigned g_kvflag[NH];
__device__ unsigned g_g1cnt[8];
__device__ unsigned g_atcnt[16];
__device__ unsigned g_fin;

__device__ __forceinline__ uint32_t smem_u32(const void* p) { return (uint32_t)__cvta_generic_to_shared(p); }
__device__ __forceinline__ void mbar_init(uint32_t bar, uint32_t cnt) {
  asm volatile("mbarrier.init.shared::cta.b64 [%0], %1;" ::"r"(bar), "r"(cnt) : "memory");
}
__device__ __forceinline__ void mbar_expect_tx(uint32_t bar, uint32_t bytes) {
  asm volatile("mbarrier.arrive.expect_tx.shared::cta.b64 _, [%0], %1;" ::"r"(bar), "r"(bytes) : "memory");
}
__device__ __forceinline__ void mbar_arrive(uint32_t bar) {
  asm volatile("mbarrier.arrive.shared::cta.b64 _, [%0];" ::"r"(bar) : "memory");
}
__device__ __forceinline__ void mbar_wait(uint32_t bar, uint32_t parity) {
  asm volatile(
      "{\n.reg .pred p;\n.reg .u32 n;\nmov.u32 n, 0;\n"
      "MW_LOOP:\nmbarrier.try_wait.parity.shared::cta.b64 p, [%0], %1;\n@p bra MW_DONE;\n"
      "add.u32 n, n, 1;\nsetp.lt.u32 p, n, 4194304;\n@p bra MW_LOOP;\ntrap;\nMW_DONE:\n}\n" ::"r"(bar), "r"(parity)
      : "memory");
}
__device__ __forceinline__ void fence_barrier_init() { asm volatile("fence.mbarrier_init.release.cluster;" ::: "memory"); }
__device__ __forceinline__ void fence_proxy_async_smem() { asm volatile("fence.proxy.async.shared::cta;" ::: "memory"); }
__device__ __forceinline__ void fence_proxy_async_gmem() { asm volatile("fence.proxy.async.global;" ::: "memory"); }
__device__ __forceinline__ void tma_load_2d(uint32_t dst, const CUtensorMap* tm, int c0, int c1, uint32_t bar) {
  asm volatile("cp.async.bulk.tensor.2d.shared::cluster.global.mbarrier::complete_tx::bytes [%0], [%1, {%3, %4}], [%2];"
               ::"r"(dst), "l"(tm), "r"(bar), "r"(c0), "r"(c1) : "memory");
}
__device__ __forceinline__ void tma_load_3d(uint32_t dst, const CUtensorMap* tm, int c0, int c1, int c2, uint32_t bar) {
  asm volatile("cp.async.bulk.tensor.3d.shared::cluster.global.mbarrier::complete_tx::bytes [%0], [%1, {%3, %4, %5}], [%2];"
               ::"r"(dst), "l"(tm), "r"(bar), "r"(c0), "r"(c1), "r"(c2) : "memory");
}
__device__ __forceinline__ void tma_load_3d_mc(uint32_t dst, const CUtensorMap* tm, int c0, int c1, int c2, uint32_t bar, uint16_t mask) {
  asm volatile("cp.async.bulk.tensor.3d.shared::cluster.global.mbarrier::complete_tx::bytes.multicast::cluster [%0], [%1, {%3, %4, %5}], [%2], %6;"
               ::"r"(dst), "l"(tm), "r"(bar), "r"(c0), "r"(c1), "r"(c2), "h"(mask) : "memory");
}
__device__ __forceinline__ void tma_store_2d(const CUtensorMap* tm, uint32_t src, int c0, int c1) {
  asm volatile("cp.async.bulk.tensor.2d.global.shared::cta.bulk_group [%0, {%2, %3}], [%1];" ::"l"(tm), "r"(src), "r"(c0), "r"(c1) : "memory");
}
__device__ __forceinline__ uint32_t mapa(uint32_t addr, uint32_t rank) {
  uint32_t r;
  asm volatile("mapa.shared::cluster.u32 %0, %1, %2;" : "=r"(r) : "r"(addr), "r"(rank));
  return r;
}
__device__ __forceinline__ void mbar_arrive_remote(uint32_t cluster_addr) {
  asm volatile("mbarrier.arrive.shared::cluster.b64 _, [%0];" ::"r"(cluster_addr) : "memory");
}
__device__ __forceinline__ void cluster_arrive() { asm volatile("barrier.cluster.arrive.release.aligned;" ::: "memory"); }
__device__ __forceinline__ void cluster_wait() { asm volatile("barrier.cluster.wait.acquire.aligned;" ::: "memory"); }
__device__ __forceinline__ void prefetch_tmap(const CUtensorMap* tm) {
  asm volatile("prefetch.tensormap [%0];" ::"l"(tm) : "memory");
}
__device__ __forceinline__ uint32_t desc_lo(uint32_t saddr, uint32_t lbo) { return ((saddr & 0x3FFFF) >> 4) | ((lbo >> 4) << 16); }
__host__ __device__ constexpr uint32_t desc_hi(uint32_t sbo, uint32_t swz) { return (sbo >> 4) | (swz << 30); }
#define WG_FENCE() asm volatile("wgmma.fence.sync.aligned;" ::: "memory")
#define WG_COMMIT() asm volatile("wgmma.commit_group.sync.aligned;" ::: "memory")
#define WG_WAIT(n) asm volatile("wgmma.wait_group.sync.aligned %0;" ::"n"(n) : "memory")
template <int N>
__device__ __forceinline__ void fence_regs(float (&d)[N]) {
#pragma unroll
  for (int i = 0; i < N; i++) asm volatile("" : "+f"(d[i])::"memory");
}
template <int N>
__device__ __forceinline__ void fence_regs_u(uint32_t (&d)[N]) {
#pragma unroll
  for (int i = 0; i < N; i++) asm volatile("" : "+r"(d[i])::"memory");
}
__device__ __forceinline__ uint32_t pack_bf16(float lo, float hi) {
  uint32_t r;
  asm("cvt.rn.bf16x2.f32 %0, %1, %2;" : "=r"(r) : "f"(hi), "f"(lo));
  return r;
}
__device__ __forceinline__ float ex2f(float x) {
  float r;
  asm("ex2.approx.ftz.f32 %0, %1;" : "=f"(r) : "f"(x));
  return r;
}
__device__ __forceinline__ float bf_lo(uint32_t v) { return __uint_as_float(v << 16); }
__device__ __forceinline__ float bf_hi(uint32_t v) { return __uint_as_float(v & 0xFFFF0000u); }
__device__ __forceinline__ uint32_t hfma2(uint32_t a, uint32_t b, uint32_t c) {
  uint32_t r;
  asm("fma.rn.f16x2 %0, %1, %2, %3;" : "=r"(r) : "r"(a), "r"(b), "r"(c));
  return r;
}

__device__ __forceinline__ void wgmma_n64_ss_tb_acc(float (&d)[32], uint32_t alo, uint32_t ahi, uint32_t blo, uint32_t bhi) {
  asm volatile("{\n.reg .pred p;\n.reg .b64 da, db;\nmov.b64 da, {%32, %33};\nmov.b64 db, {%34, %35};\nsetp.eq.b32 p, 0, 0;\n"
  "wgmma.mma_async.sync.aligned.m64n64k16.f32.bf16.bf16 {%0,%1,%2,%3,%4,%5,%6,%7,%8,%9,%10,%11,%12,%13,%14,%15,%16,%17,%18,%19,%20,%21,%22,%23,%24,%25,%26,%27,%28,%29,%30,%31}, da, db, p, 1, 1, 0, 1;\n}\n"
   : "+f"(d[0]),"+f"(d[1]),"+f"(d[2]),"+f"(d[3]),"+f"(d[4]),"+f"(d[5]),"+f"(d[6]),"+f"(d[7]),"+f"(d[8]),"+f"(d[9]),"+f"(d[10]),"+f"(d[11]),"+f"(d[12]),"+f"(d[13]),"+f"(d[14]),"+f"(d[15]),"+f"(d[16]),"+f"(d[17]),"+f"(d[18]),"+f"(d[19]),"+f"(d[20]),"+f"(d[21]),"+f"(d[22]),"+f"(d[23]),"+f"(d[24]),"+f"(d[25]),"+f"(d[26]),"+f"(d[27]),"+f"(d[28]),"+f"(d[29]),"+f"(d[30]),"+f"(d[31])
   : "r"(alo),"r"(ahi),"r"(blo),"r"(bhi));
}
__device__ __forceinline__ void wgmma_n64_ss_tb_init(float (&d)[32], uint32_t alo, uint32_t ahi, uint32_t blo, uint32_t bhi) {
  asm volatile("{\n.reg .pred p;\n.reg .b64 da, db;\nmov.b64 da, {%32, %33};\nmov.b64 db, {%34, %35};\nsetp.ne.b32 p, 0, 0;\n"
  "wgmma.mma_async.sync.aligned.m64n64k16.f32.bf16.bf16 {%0,%1,%2,%3,%4,%5,%6,%7,%8,%9,%10,%11,%12,%13,%14,%15,%16,%17,%18,%19,%20,%21,%22,%23,%24,%25,%26,%27,%28,%29,%30,%31}, da, db, p, 1, 1, 0, 1;\n}\n"
   : "=f"(d[0]),"=f"(d[1]),"=f"(d[2]),"=f"(d[3]),"=f"(d[4]),"=f"(d[5]),"=f"(d[6]),"=f"(d[7]),"=f"(d[8]),"=f"(d[9]),"=f"(d[10]),"=f"(d[11]),"=f"(d[12]),"=f"(d[13]),"=f"(d[14]),"=f"(d[15]),"=f"(d[16]),"=f"(d[17]),"=f"(d[18]),"=f"(d[19]),"=f"(d[20]),"=f"(d[21]),"=f"(d[22]),"=f"(d[23]),"=f"(d[24]),"=f"(d[25]),"=f"(d[26]),"=f"(d[27]),"=f"(d[28]),"=f"(d[29]),"=f"(d[30]),"=f"(d[31])
   : "r"(alo),"r"(ahi),"r"(blo),"r"(bhi));
}
__device__ __forceinline__ void wgmma_n96_ss_tb_acc(float (&d)[48], uint32_t alo, uint32_t ahi, uint32_t blo, uint32_t bhi) {
  asm volatile("{\n.reg .pred p;\n.reg .b64 da, db;\nmov.b64 da, {%48, %49};\nmov.b64 db, {%50, %51};\nsetp.eq.b32 p, 0, 0;\n"
  "wgmma.mma_async.sync.aligned.m64n96k16.f32.bf16.bf16 {%0,%1,%2,%3,%4,%5,%6,%7,%8,%9,%10,%11,%12,%13,%14,%15,%16,%17,%18,%19,%20,%21,%22,%23,%24,%25,%26,%27,%28,%29,%30,%31,%32,%33,%34,%35,%36,%37,%38,%39,%40,%41,%42,%43,%44,%45,%46,%47}, da, db, p, 1, 1, 0, 1;\n}\n"
   : "+f"(d[0]),"+f"(d[1]),"+f"(d[2]),"+f"(d[3]),"+f"(d[4]),"+f"(d[5]),"+f"(d[6]),"+f"(d[7]),"+f"(d[8]),"+f"(d[9]),"+f"(d[10]),"+f"(d[11]),"+f"(d[12]),"+f"(d[13]),"+f"(d[14]),"+f"(d[15]),"+f"(d[16]),"+f"(d[17]),"+f"(d[18]),"+f"(d[19]),"+f"(d[20]),"+f"(d[21]),"+f"(d[22]),"+f"(d[23]),"+f"(d[24]),"+f"(d[25]),"+f"(d[26]),"+f"(d[27]),"+f"(d[28]),"+f"(d[29]),"+f"(d[30]),"+f"(d[31]),"+f"(d[32]),"+f"(d[33]),"+f"(d[34]),"+f"(d[35]),"+f"(d[36]),"+f"(d[37]),"+f"(d[38]),"+f"(d[39]),"+f"(d[40]),"+f"(d[41]),"+f"(d[42]),"+f"(d[43]),"+f"(d[44]),"+f"(d[45]),"+f"(d[46]),"+f"(d[47])
   : "r"(alo),"r"(ahi),"r"(blo),"r"(bhi));
}
__device__ __forceinline__ void wgmma_n96_ss_tb_init(float (&d)[48], uint32_t alo, uint32_t ahi, uint32_t blo, uint32_t bhi) {
  asm volatile("{\n.reg .pred p;\n.reg .b64 da, db;\nmov.b64 da, {%48, %49};\nmov.b64 db, {%50, %51};\nsetp.ne.b32 p, 0, 0;\n"
  "wgmma.mma_async.sync.aligned.m64n96k16.f32.bf16.bf16 {%0,%1,%2,%3,%4,%5,%6,%7,%8,%9,%10,%11,%12,%13,%14,%15,%16,%17,%18,%19,%20,%21,%22,%23,%24,%25,%26,%27,%28,%29,%30,%31,%32,%33,%34,%35,%36,%37,%38,%39,%40,%41,%42,%43,%44,%45,%46,%47}, da, db, p, 1, 1, 0, 1;\n}\n"
   : "=f"(d[0]),"=f"(d[1]),"=f"(d[2]),"=f"(d[3]),"=f"(d[4]),"=f"(d[5]),"=f"(d[6]),"=f"(d[7]),"=f"(d[8]),"=f"(d[9]),"=f"(d[10]),"=f"(d[11]),"=f"(d[12]),"=f"(d[13]),"=f"(d[14]),"=f"(d[15]),"=f"(d[16]),"=f"(d[17]),"=f"(d[18]),"=f"(d[19]),"=f"(d[20]),"=f"(d[21]),"=f"(d[22]),"=f"(d[23]),"=f"(d[24]),"=f"(d[25]),"=f"(d[26]),"=f"(d[27]),"=f"(d[28]),"=f"(d[29]),"=f"(d[30]),"=f"(d[31]),"=f"(d[32]),"=f"(d[33]),"=f"(d[34]),"=f"(d[35]),"=f"(d[36]),"=f"(d[37]),"=f"(d[38]),"=f"(d[39]),"=f"(d[40]),"=f"(d[41]),"=f"(d[42]),"=f"(d[43]),"=f"(d[44]),"=f"(d[45]),"=f"(d[46]),"=f"(d[47])
   : "r"(alo),"r"(ahi),"r"(blo),"r"(bhi));
}
__device__ __forceinline__ void wgmma_n128_rs_init(float (&d)[64], uint32_t a0, uint32_t a1, uint32_t a2, uint32_t a3, uint32_t blo, uint32_t bhi) {
  asm volatile("{\n.reg .pred p;\n.reg .b64 da, db;\nmov.b64 db, {%68, %69};\nsetp.ne.b32 p, 0, 0;\n"
  "wgmma.mma_async.sync.aligned.m64n128k16.f32.bf16.bf16 {%0,%1,%2,%3,%4,%5,%6,%7,%8,%9,%10,%11,%12,%13,%14,%15,%16,%17,%18,%19,%20,%21,%22,%23,%24,%25,%26,%27,%28,%29,%30,%31,%32,%33,%34,%35,%36,%37,%38,%39,%40,%41,%42,%43,%44,%45,%46,%47,%48,%49,%50,%51,%52,%53,%54,%55,%56,%57,%58,%59,%60,%61,%62,%63}, {%64,%65,%66,%67}, db, p, 1, 1, 0;\n}\n"
   : "=f"(d[0]),"=f"(d[1]),"=f"(d[2]),"=f"(d[3]),"=f"(d[4]),"=f"(d[5]),"=f"(d[6]),"=f"(d[7]),"=f"(d[8]),"=f"(d[9]),"=f"(d[10]),"=f"(d[11]),"=f"(d[12]),"=f"(d[13]),"=f"(d[14]),"=f"(d[15]),"=f"(d[16]),"=f"(d[17]),"=f"(d[18]),"=f"(d[19]),"=f"(d[20]),"=f"(d[21]),"=f"(d[22]),"=f"(d[23]),"=f"(d[24]),"=f"(d[25]),"=f"(d[26]),"=f"(d[27]),"=f"(d[28]),"=f"(d[29]),"=f"(d[30]),"=f"(d[31]),"=f"(d[32]),"=f"(d[33]),"=f"(d[34]),"=f"(d[35]),"=f"(d[36]),"=f"(d[37]),"=f"(d[38]),"=f"(d[39]),"=f"(d[40]),"=f"(d[41]),"=f"(d[42]),"=f"(d[43]),"=f"(d[44]),"=f"(d[45]),"=f"(d[46]),"=f"(d[47]),"=f"(d[48]),"=f"(d[49]),"=f"(d[50]),"=f"(d[51]),"=f"(d[52]),"=f"(d[53]),"=f"(d[54]),"=f"(d[55]),"=f"(d[56]),"=f"(d[57]),"=f"(d[58]),"=f"(d[59]),"=f"(d[60]),"=f"(d[61]),"=f"(d[62]),"=f"(d[63])
   : "r"(a0),"r"(a1),"r"(a2),"r"(a3),"r"(blo),"r"(bhi));
}
__device__ __forceinline__ void wgmma_n128_rs_acc(float (&d)[64], uint32_t a0, uint32_t a1, uint32_t a2, uint32_t a3, uint32_t blo, uint32_t bhi) {
  asm volatile("{\n.reg .pred p;\n.reg .b64 da, db;\nmov.b64 db, {%68, %69};\nsetp.eq.b32 p, 0, 0;\n"
  "wgmma.mma_async.sync.aligned.m64n128k16.f32.bf16.bf16 {%0,%1,%2,%3,%4,%5,%6,%7,%8,%9,%10,%11,%12,%13,%14,%15,%16,%17,%18,%19,%20,%21,%22,%23,%24,%25,%26,%27,%28,%29,%30,%31,%32,%33,%34,%35,%36,%37,%38,%39,%40,%41,%42,%43,%44,%45,%46,%47,%48,%49,%50,%51,%52,%53,%54,%55,%56,%57,%58,%59,%60,%61,%62,%63}, {%64,%65,%66,%67}, db, p, 1, 1, 0;\n}\n"
   : "+f"(d[0]),"+f"(d[1]),"+f"(d[2]),"+f"(d[3]),"+f"(d[4]),"+f"(d[5]),"+f"(d[6]),"+f"(d[7]),"+f"(d[8]),"+f"(d[9]),"+f"(d[10]),"+f"(d[11]),"+f"(d[12]),"+f"(d[13]),"+f"(d[14]),"+f"(d[15]),"+f"(d[16]),"+f"(d[17]),"+f"(d[18]),"+f"(d[19]),"+f"(d[20]),"+f"(d[21]),"+f"(d[22]),"+f"(d[23]),"+f"(d[24]),"+f"(d[25]),"+f"(d[26]),"+f"(d[27]),"+f"(d[28]),"+f"(d[29]),"+f"(d[30]),"+f"(d[31]),"+f"(d[32]),"+f"(d[33]),"+f"(d[34]),"+f"(d[35]),"+f"(d[36]),"+f"(d[37]),"+f"(d[38]),"+f"(d[39]),"+f"(d[40]),"+f"(d[41]),"+f"(d[42]),"+f"(d[43]),"+f"(d[44]),"+f"(d[45]),"+f"(d[46]),"+f"(d[47]),"+f"(d[48]),"+f"(d[49]),"+f"(d[50]),"+f"(d[51]),"+f"(d[52]),"+f"(d[53]),"+f"(d[54]),"+f"(d[55]),"+f"(d[56]),"+f"(d[57]),"+f"(d[58]),"+f"(d[59]),"+f"(d[60]),"+f"(d[61]),"+f"(d[62]),"+f"(d[63])
   : "r"(a0),"r"(a1),"r"(a2),"r"(a3),"r"(blo),"r"(bhi));
}
__device__ __forceinline__ void wgmma_n64_rs_init(float (&d)[32], uint32_t a0, uint32_t a1, uint32_t a2, uint32_t a3, uint32_t blo, uint32_t bhi) {
  asm volatile("{\n.reg .pred p;\n.reg .b64 da, db;\nmov.b64 db, {%36, %37};\nsetp.ne.b32 p, 0, 0;\n"
  "wgmma.mma_async.sync.aligned.m64n64k16.f32.bf16.bf16 {%0,%1,%2,%3,%4,%5,%6,%7,%8,%9,%10,%11,%12,%13,%14,%15,%16,%17,%18,%19,%20,%21,%22,%23,%24,%25,%26,%27,%28,%29,%30,%31}, {%32,%33,%34,%35}, db, p, 1, 1, 0;\n}\n"
   : "=f"(d[0]),"=f"(d[1]),"=f"(d[2]),"=f"(d[3]),"=f"(d[4]),"=f"(d[5]),"=f"(d[6]),"=f"(d[7]),"=f"(d[8]),"=f"(d[9]),"=f"(d[10]),"=f"(d[11]),"=f"(d[12]),"=f"(d[13]),"=f"(d[14]),"=f"(d[15]),"=f"(d[16]),"=f"(d[17]),"=f"(d[18]),"=f"(d[19]),"=f"(d[20]),"=f"(d[21]),"=f"(d[22]),"=f"(d[23]),"=f"(d[24]),"=f"(d[25]),"=f"(d[26]),"=f"(d[27]),"=f"(d[28]),"=f"(d[29]),"=f"(d[30]),"=f"(d[31])
   : "r"(a0),"r"(a1),"r"(a2),"r"(a3),"r"(blo),"r"(bhi));
}
__device__ __forceinline__ void wgmma_n64_rs_acc(float (&d)[32], uint32_t a0, uint32_t a1, uint32_t a2, uint32_t a3, uint32_t blo, uint32_t bhi) {
  asm volatile("{\n.reg .pred p;\n.reg .b64 da, db;\nmov.b64 db, {%36, %37};\nsetp.eq.b32 p, 0, 0;\n"
  "wgmma.mma_async.sync.aligned.m64n64k16.f32.bf16.bf16 {%0,%1,%2,%3,%4,%5,%6,%7,%8,%9,%10,%11,%12,%13,%14,%15,%16,%17,%18,%19,%20,%21,%22,%23,%24,%25,%26,%27,%28,%29,%30,%31}, {%32,%33,%34,%35}, db, p, 1, 1, 0;\n}\n"
   : "+f"(d[0]),"+f"(d[1]),"+f"(d[2]),"+f"(d[3]),"+f"(d[4]),"+f"(d[5]),"+f"(d[6]),"+f"(d[7]),"+f"(d[8]),"+f"(d[9]),"+f"(d[10]),"+f"(d[11]),"+f"(d[12]),"+f"(d[13]),"+f"(d[14]),"+f"(d[15]),"+f"(d[16]),"+f"(d[17]),"+f"(d[18]),"+f"(d[19]),"+f"(d[20]),"+f"(d[21]),"+f"(d[22]),"+f"(d[23]),"+f"(d[24]),"+f"(d[25]),"+f"(d[26]),"+f"(d[27]),"+f"(d[28]),"+f"(d[29]),"+f"(d[30]),"+f"(d[31])
   : "r"(a0),"r"(a1),"r"(a2),"r"(a3),"r"(blo),"r"(bhi));
}
__device__ __forceinline__ void wgmma_n24_rs_tb(float (&d)[12], uint32_t a0, uint32_t a1, uint32_t a2, uint32_t a3, uint32_t blo, uint32_t bhi, int sc) {
  asm volatile("{\n.reg .pred p;\n.reg .b64 da, db;\nmov.b64 db, {%16, %17};\nsetp.ne.b32 p, %18, 0;\n"
  "wgmma.mma_async.sync.aligned.m64n24k16.f32.bf16.bf16 {%0,%1,%2,%3,%4,%5,%6,%7,%8,%9,%10,%11}, {%12,%13,%14,%15}, db, p, 1, 1, 1;\n}\n"
   : "+f"(d[0]),"+f"(d[1]),"+f"(d[2]),"+f"(d[3]),"+f"(d[4]),"+f"(d[5]),"+f"(d[6]),"+f"(d[7]),"+f"(d[8]),"+f"(d[9]),"+f"(d[10]),"+f"(d[11])
   : "r"(a0),"r"(a1),"r"(a2),"r"(a3),"r"(blo),"r"(bhi),"r"(sc));
}
__device__ __forceinline__ void wgmma_n24_rs_tb_init(float (&d)[12], uint32_t a0, uint32_t a1, uint32_t a2, uint32_t a3, uint32_t blo, uint32_t bhi) {
  asm volatile("{\n.reg .pred p;\n.reg .b64 da, db;\nmov.b64 db, {%16, %17};\nsetp.ne.b32 p, 0, 0;\n"
  "wgmma.mma_async.sync.aligned.m64n24k16.f32.bf16.bf16 {%0,%1,%2,%3,%4,%5,%6,%7,%8,%9,%10,%11}, {%12,%13,%14,%15}, db, p, 1, 1, 1;\n}\n"
   : "=f"(d[0]),"=f"(d[1]),"=f"(d[2]),"=f"(d[3]),"=f"(d[4]),"=f"(d[5]),"=f"(d[6]),"=f"(d[7]),"=f"(d[8]),"=f"(d[9]),"=f"(d[10]),"=f"(d[11])
   : "r"(a0),"r"(a1),"r"(a2),"r"(a3),"r"(blo),"r"(bhi));
}
__device__ __forceinline__ void wgmma_n24_rs_tb_acc(float (&d)[12], uint32_t a0, uint32_t a1, uint32_t a2, uint32_t a3, uint32_t blo, uint32_t bhi) {
  asm volatile("{\n.reg .pred p;\n.reg .b64 da, db;\nmov.b64 db, {%16, %17};\nsetp.eq.b32 p, 0, 0;\n"
  "wgmma.mma_async.sync.aligned.m64n24k16.f32.bf16.bf16 {%0,%1,%2,%3,%4,%5,%6,%7,%8,%9,%10,%11}, {%12,%13,%14,%15}, db, p, 1, 1, 1;\n}\n"
   : "+f"(d[0]),"+f"(d[1]),"+f"(d[2]),"+f"(d[3]),"+f"(d[4]),"+f"(d[5]),"+f"(d[6]),"+f"(d[7]),"+f"(d[8]),"+f"(d[9]),"+f"(d[10]),"+f"(d[11])
   : "r"(a0),"r"(a1),"r"(a2),"r"(a3),"r"(blo),"r"(bhi));
}
__device__ __forceinline__ void wgmma_n24_ss_tatb_init(float (&d)[12], uint32_t alo, uint32_t ahi, uint32_t blo, uint32_t bhi) {
  asm volatile("{\n.reg .pred p;\n.reg .b64 da, db;\nmov.b64 da, {%12, %13};\nmov.b64 db, {%14, %15};\nsetp.ne.b32 p, 0, 0;\n"
  "wgmma.mma_async.sync.aligned.m64n24k16.f32.bf16.bf16 {%0,%1,%2,%3,%4,%5,%6,%7,%8,%9,%10,%11}, da, db, p, 1, 1, 1, 1;\n}\n"
   : "=f"(d[0]),"=f"(d[1]),"=f"(d[2]),"=f"(d[3]),"=f"(d[4]),"=f"(d[5]),"=f"(d[6]),"=f"(d[7]),"=f"(d[8]),"=f"(d[9]),"=f"(d[10]),"=f"(d[11])
   : "r"(alo),"r"(ahi),"r"(blo),"r"(bhi));
}
__device__ __forceinline__ void wgmma_n24_ss_tatb_acc(float (&d)[12], uint32_t alo, uint32_t ahi, uint32_t blo, uint32_t bhi) {
  asm volatile("{\n.reg .pred p;\n.reg .b64 da, db;\nmov.b64 da, {%12, %13};\nmov.b64 db, {%14, %15};\nsetp.eq.b32 p, 0, 0;\n"
  "wgmma.mma_async.sync.aligned.m64n24k16.f32.bf16.bf16 {%0,%1,%2,%3,%4,%5,%6,%7,%8,%9,%10,%11}, da, db, p, 1, 1, 1, 1;\n}\n"
   : "+f"(d[0]),"+f"(d[1]),"+f"(d[2]),"+f"(d[3]),"+f"(d[4]),"+f"(d[5]),"+f"(d[6]),"+f"(d[7]),"+f"(d[8]),"+f"(d[9]),"+f"(d[10]),"+f"(d[11])
   : "r"(alo),"r"(ahi),"r"(blo),"r"(bhi));
}

template <int N, int OFF>
__device__ __forceinline__ float (&subacc(float (&a)[80]))[N] { return reinterpret_cast<float(&)[N]>(a[OFF]); }
template <bool INIT>
__device__ __forceinline__ void mma_160(float (&acc)[80], uint32_t alo, uint32_t ahi, uint32_t blo, uint32_t bhi, uint32_t gs16) {
  if (INIT) { wgmma_n64_ss_tb_init(subacc<32, 0>(acc), alo, ahi, blo, bhi); wgmma_n96_ss_tb_init(subacc<48, 32>(acc), alo, ahi, blo + 2 * gs16, bhi); }
  else { wgmma_n64_ss_tb_acc(subacc<32, 0>(acc), alo, ahi, blo, bhi); wgmma_n96_ss_tb_acc(subacc<48, 32>(acc), alo, ahi, blo + 2 * gs16, bhi); }
}

constexpr int G1_A_BYTES = 10 * 16384;
constexpr int G1_BST = 6;
constexpr int G1_B_BYTES = 10240;

constexpr uint32_t HSTRIDE = NMT * 2 * HB;
__device__ __forceinline__ uint32_t badd2(uint32_t a, uint32_t b) {
  uint32_t r;
  asm("add.rn.bf16x2 %0, %1, %2;" : "=r"(r) : "r"(a), "r"(b));
  return r;
}
__device__ __forceinline__ uint32_t bmax2(uint32_t a, uint32_t b) {
  uint32_t r;
  asm("max.bf16x2 %0, %1, %2;" : "=r"(r) : "r"(a), "r"(b));
  return r;
}
__device__ __forceinline__ uint32_t phi_pair(float a, float b) {
  const float ea = ex2f(fminf(a * 1.4426950408889634f, 0.f)) + 1e-6f, eb = ex2f(fminf(b * 1.4426950408889634f, 0.f)) + 1e-6f;
  return pack_bf16(fmaxf(a, 0.f) + ea, fmaxf(b, 0.f) + eb);
}

template <int KIND>
__device__ __forceinline__ void g1_epilogue(float (&acc)[80], uint8_t* base, int row, int lane,
                                            float* nrm  ) {
  const int c = lane & 3;
  uint8_t* ptr = base + row * 16 + c * 4;
  uint32_t pad0 = 0, pad1 = 0;
  if (KIND == 2) {
#pragma unroll
    for (int i = 0; i < 2; i++) {
      const int r = row + 8 * i;
      const bool mufu = (MUFU_MASK >> (r >> 3)) & 1;
      uint32_t s0, s1, s3;
      if (mufu) { s0 = 0; s1 = 0x4280; s3 = 0; }
      else { s0 = 0x4780; s1 = 0x433F; s3 = POLY_FINE; }
      const uint32_t v = (c & 1) ? (0x3F80u | (s3 << 16)) : (s0 | (s1 << 16));
      if (i == 0) pad0 = v; else pad1 = v;
    }
  } else if (KIND == 3) {
    pad0 = (c & 1) ? 0u : 0x3F80u; pad1 = pad0;
  }
#pragma unroll
  for (int p = 0; p < 4; p++) {
    float ne0 = 0.f, ne1 = 0.f, no0 = 0.f, no1 = 0.f, nm0, nm1;
    uint8_t* pe = ptr + 2 * p * HSTRIDE;
    uint8_t* po = pe + HSTRIDE;
#pragma unroll
    for (int bb = 0; bb < 5; bb++) {
      const int b = 5 * p + bb;
      float v0 = acc[4 * b], v1 = acc[4 * b + 1], v2 = acc[4 * b + 2], v3 = acc[4 * b + 3];
      uint32_t w0, w1;
      if (KIND == 0) { w0 = phi_pair(v0, v1); w1 = phi_pair(v2, v3); }
      else if (KIND == 1) { w0 = pack_bf16(v0 * QSCALE, v1 * QSCALE); w1 = pack_bf16(v2 * QSCALE, v3 * QSCALE); }
      else { w0 = pack_bf16(v0, v1); w1 = pack_bf16(v2, v3); }
      if (bb < 2) {
        *reinterpret_cast<uint32_t*>(pe + bb * CHB) = w0;
        *reinterpret_cast<uint32_t*>(pe + bb * CHB + 128) = w1;
      } else if (bb > 2) {
        *reinterpret_cast<uint32_t*>(po + (bb - 2) * CHB) = w0;
        *reinterpret_cast<uint32_t*>(po + (bb - 2) * CHB + 128) = w1;
      } else {
        *reinterpret_cast<uint32_t*>(pe + 2 * CHB) = c < 2 ? w0 : pad0;
        *reinterpret_cast<uint32_t*>(pe + 2 * CHB + 128) = c < 2 ? w1 : pad1;
        *reinterpret_cast<uint32_t*>(po) = c < 2 ? pad0 : w0;
        *reinterpret_cast<uint32_t*>(po + 128) = c < 2 ? pad1 : w1;
      }
      if (KIND == 1 || KIND == 2) {
        if (bb < 2) { ne0 = fmaf(v0, v0, fmaf(v1, v1, ne0)); ne1 = fmaf(v2, v2, fmaf(v3, v3, ne1)); }
        else if (bb > 2) { no0 = fmaf(v0, v0, fmaf(v1, v1, no0)); no1 = fmaf(v2, v2, fmaf(v3, v3, no1)); }
        else { nm0 = fmaf(v0, v0, v1 * v1); nm1 = fmaf(v2, v2, v3 * v3); }
      }
    }
    if (KIND == 1 || KIND == 2) {
      if (c < 2) { ne0 += nm0; ne1 += nm1; } else { no0 += nm0; no1 += nm1; }
      uint32_t r0 = pack_bf16(ne0, no0), r1 = pack_bf16(ne1, no1);
#pragma unroll
      for (int o = 1; o <= 2; o <<= 1) {
        r0 = badd2(r0, __shfl_xor_sync(~0u, r0, o));
        r1 = badd2(r1, __shfl_xor_sync(~0u, r1, o));
      }
      uint32_t m = bmax2(r0, r1);
#pragma unroll
      for (int o = 4; o <= 16; o <<= 1) m = bmax2(m, __shfl_xor_sync(~0u, m, o));
      constexpr float INFL = (KIND == 1 ? QSCALE * QSCALE : 1.0f) * 1.03f;
      if (lane == 0) { nrm[(2 * p) * 128] = bf_lo(m) * INFL; nrm[(2 * p + 1) * 128] = bf_hi(m) * INFL; }
    }
  }
}

__device__ __forceinline__ void g1_tile(int t, uint32_t a_lo0, uint32_t b_lo0, uint32_t fullA, uint32_t fullB, uint32_t emptyB,
                                        uint32_t order, int lane, int kind, uint8_t* base, int row, float* nrm, uint32_t emptyR, uint32_t afree, uint32_t yield) {
  float acc[80];
  constexpr uint32_t a_hi = desc_hi(1024, 1), b_hi = desc_hi(512, 2);
  const int step = 1;
  int s = (t * 20) % G1_BST, ph = ((t * 20) / G1_BST) & 1, sp;
#define FIRSTA (t == 0)
  {
    if (FIRSTA) mbar_wait(fullA, 0);
    mbar_wait(fullB + 8 * s, ph);
    const uint32_t blo = b_lo0 + s * (G1_B_BYTES >> 4);
    WG_FENCE();
    mma_160<true>(acc, a_lo0, a_hi, blo, b_hi, 128);
    mma_160<false>(acc, a_lo0 + 2, a_hi, blo + 64, b_hi, 128);
    WG_COMMIT();
    sp = s;
    s += step;
    if (s >= G1_BST) { s -= G1_BST; ph ^= 1; }
  }
#pragma unroll 1
  for (int kb = 1; kb < 20; kb++) {
    if (FIRSTA && !(kb & 1)) mbar_wait(fullA + 8 * (kb >> 1), 0);
    mbar_wait(fullB + 8 * s, ph);
    if (kb == 19 && t < 2 && lane == 0) mbar_arrive(order + 8 * t);
    const uint32_t alo = a_lo0 + (kb >> 1) * 1024 + (kb & 1) * 4, blo = b_lo0 + s * (G1_B_BYTES >> 4);
    WG_FENCE();
    mma_160<false>(acc, alo, a_hi, blo, b_hi, 128);
    mma_160<false>(acc, alo + 2, a_hi, blo + 64, b_hi, 128);
    WG_COMMIT();
    WG_WAIT(1);
    if (lane == 0) {
      mbar_arrive(emptyB + 8 * sp); mbar_arrive_remote(emptyR + 8 * sp);
      if (t == 2 && !(kb & 1)) mbar_arrive(afree + 4 * kb - 8);
    }
    sp = s;
    s += step;
    if (s >= G1_BST) { s -= G1_BST; ph ^= 1; }
  }
  WG_WAIT(0);
  fence_regs(acc);
  if (lane == 0) { mbar_arrive(emptyB + 8 * sp); mbar_arrive_remote(emptyR + 8 * sp); }
  if (kind == 0) g1_epilogue<0>(acc, base, row, lane, nrm);
  else if (kind == 1) g1_epilogue<1>(acc, base, row, lane, nrm);
  else if (kind == 2) g1_epilogue<2>(acc, base, row, lane, nrm);
  else g1_epilogue<3>(acc, base, row, lane, nrm);
}

constexpr int AT_KV = 2 * HB;

struct PolyConst { uint32_t a2; };
__device__ __forceinline__ uint32_t exp2_poly_pair(float t0, float t1, const PolyConst& k) {
  uint32_t u = __byte_perm(__float_as_uint(t0), __float_as_uint(t1), 0x5410);
  uint32_t z = u & 0x007F007Fu;
  uint32_t q = hfma2(k.a2, z, 0xB560B560u);
  q = hfma2(q, z, 0x00100010u);
  return u + q;
}

__device__ __forceinline__ void store_o(float (&o)[12], float sc0, float sc1, uint8_t* dst  , int colbase, int c, int odd) {
#pragma unroll
  for (int b = 0; b < 3; b++) {
    const int slot = 8 * b + 2 * c;
    if (odd ? slot >= 4 : slot < 20) {
      const int col = colbase + slot;
      uint8_t* q = dst + (col >> 3) * CHB + (col & 7) * 2;
      *reinterpret_cast<uint32_t*>(q) = pack_bf16(o[4 * b] * sc0, o[4 * b + 1] * sc0);
      *reinterpret_cast<uint32_t*>(q + 128) = pack_bf16(o[4 * b + 2] * sc1, o[4 * b + 3] * sc1);
    }
  }
}
__device__ __forceinline__ void row_sums(const float (&o)[12], int lane, int odd, float& l0, float& l1) {
  const int src = (lane & ~3) | (odd ? 0 : 2);
  l0 = __shfl_sync(~0u, odd ? o[0] : o[8], src);
  l1 = __shfl_sync(~0u, odd ? o[2] : o[10], src);
}

struct Frag6 { uint32_t a0, a1, a2, a3, b0, b1; };
__device__ __forceinline__ uint32_t ldcg32(const uint8_t* p) { return __ldcg(reinterpret_cast<const uint32_t*>(p)); }
__device__ __forceinline__ Frag6 load_frag(const uint8_t* src  , int cA, int cB) {
  Frag6 f;
  const uint8_t* pa = src + cA * CHB;
  const uint8_t* pb = src + cB * CHB;
  f.a0 = ldcg32(pa); f.a1 = ldcg32(pa + 128);
  f.a2 = ldcg32(pa + CHB); f.a3 = ldcg32(pa + CHB + 128);
  f.b0 = ldcg32(pb); f.b1 = ldcg32(pb + 128);
  return f;
}

struct AttnCtx {
  uint32_t sKV, full, kvaFull, kvdone, kvfree;
  int h, wg, w4, lane;
  uint32_t kA, kB;
};

#define KVJT 10
constexpr int KVA_OFF = 198656;
constexpr uint32_t KD_HI = desc_hi(128, 0);
constexpr uint32_t VD_HI = desc_hi(CHB, 0);

__device__ __forceinline__ void kv_partial(const AttnCtx& x) {
  float kv[12];
  mbar_wait(x.kvaFull + (x.wg < 2 ? 8 : 0), 0);
  const uint32_t alo = desc_lo(x.sKV + KVA_OFF + (x.wg & 1) * AT_KV, 128), blo = alo + (HB >> 4);
  WG_FENCE();
  wgmma_n24_ss_tatb_init(kv, alo, VD_HI, blo, VD_HI);
#pragma unroll
  for (int kk = 1; kk < 8; kk++) wgmma_n24_ss_tatb_acc(kv, alo + kk * 16, VD_HI, blo + kk * 16, VD_HI);
  WG_COMMIT();
  WG_WAIT(0);
  fence_regs(kv);
  if (x.w4 < 2) {
    const int g = x.lane >> 2, c = x.lane & 3;
    float* dst = g_kvpart + x.h * 576 + (x.w4 * 16 + g) * 24 + 2 * c;
    const int d0 = x.w4 * 16 + g;
#pragma unroll
    for (int b = 0; b < 3; b++) {
      if (d0 < 24) asm volatile("red.global.add.v2.f32 [%0], {%1, %2};" ::"l"(dst + 8 * b), "f"(kv[4 * b]), "f"(kv[4 * b + 1]) : "memory");
      if (d0 + 8 < 24) asm volatile("red.global.add.v2.f32 [%0], {%1, %2};" ::"l"(dst + 8 * 24 + 8 * b), "f"(kv[4 * b + 2]), "f"(kv[4 * b + 3]) : "memory");
    }
  }
  __syncwarp();
  if (x.lane == 0) mbar_arrive(x.kvdone + (x.wg < 2 ? 8 : 0));
}

template <int PASS>
__device__ __forceinline__ void pass_fast(const AttnCtx& x, const Frag6& q, float (&o)[12]) {
  PolyConst pc;
  pc.a2 = 0x793D793Du;
  asm volatile("" : "+r"(pc.a2));
  constexpr uint32_t T = AT_KV >> 4;
  uint32_t klo0 = desc_lo(x.sKV + x.kA, CHB);
  uint32_t klo2 = desc_lo(x.sKV + x.kB, 0);
  uint32_t vlo = desc_lo(x.sKV + HB, 128);
  uint32_t p[32];
#pragma unroll 1
  for (int jt = 0; jt < 16; jt++) {
    float s[64];
    if (PASS == 0) mbar_wait(x.full + 8 * jt, 0);
    WG_WAIT(0);
    fence_regs_u(p);
    if (PASS == 1 && jt > 0 && x.lane == 0) mbar_arrive(x.kvfree + 8 * jt - 8);
    if (PASS == 0) {
      if (jt == KVJT) kv_partial(x);
    }
    WG_FENCE();
    wgmma_n128_rs_init(s, q.a0, q.a1, q.a2, q.a3, klo0, KD_HI);
    wgmma_n128_rs_acc(s, q.b0, q.b1, 0u, 0u, klo2, KD_HI);
    WG_COMMIT();
    WG_WAIT(0);
    fence_regs(s);
#pragma unroll
    for (int qt = 0; qt < 4; qt++) {
#pragma unroll
      for (int b = 4 * qt; b < 4 * qt + 4; b++) {
        if ((MUFU_MASK >> b) & 1) {
          p[2 * b] = pack_bf16(ex2f(s[4 * b]), ex2f(s[4 * b + 1]));
          p[2 * b + 1] = pack_bf16(ex2f(s[4 * b + 2]), ex2f(s[4 * b + 3]));
        } else {
          p[2 * b] = exp2_poly_pair(s[4 * b], s[4 * b + 1], pc);
          p[2 * b + 1] = exp2_poly_pair(s[4 * b + 2], s[4 * b + 3], pc);
        }
      }
      WG_FENCE();
      if (qt == 0) wgmma_n24_rs_tb(o, p[0], p[1], p[2], p[3], vlo, VD_HI, jt != 0);
      else wgmma_n24_rs_tb_acc(o, p[8 * qt], p[8 * qt + 1], p[8 * qt + 2], p[8 * qt + 3], vlo + qt * 32, VD_HI);
      wgmma_n24_rs_tb_acc(o, p[8 * qt + 4], p[8 * qt + 5], p[8 * qt + 6], p[8 * qt + 7], vlo + qt * 32 + 16, VD_HI);
    }
    WG_COMMIT();
    klo0 += T; klo2 += T; vlo += T;
  }
  WG_WAIT(0);
  fence_regs(o);
}

__device__ __forceinline__ void pass_slow(const AttnCtx& x, const Frag6& q, float (&o)[12], int pass) {
  float m0 = -INFINITY, m1 = -INFINITY;
#pragma unroll
  for (int i = 0; i < 12; i++) o[i] = 0.f;
  fence_regs(o);
#pragma unroll 1
  for (int it = 0; it < 32; it++) {
    const int jt = it >> 1;
    if (pass == 0) {
      if (it == 2 * KVJT) kv_partial(x);
      mbar_wait(x.full + 8 * jt, 0);
    }
    float s2[32];
    uint32_t p2[16];
    const uint32_t kb = x.sKV + jt * AT_KV + (it & 1) * 1024;
    WG_FENCE();
    wgmma_n64_rs_init(s2, q.a0, q.a1, q.a2, q.a3, desc_lo(kb + x.kA, CHB), KD_HI);
    wgmma_n64_rs_acc(s2, q.b0, q.b1, 0u, 0u, desc_lo(kb + x.kB, 0), KD_HI);
    WG_COMMIT();
    WG_WAIT(0);
    fence_regs(s2);
    float x0 = m0, x1 = m1;
#pragma unroll
    for (int b = 0; b < 8; b++) {
      x0 = fmaxf(x0, fmaxf(s2[4 * b], s2[4 * b + 1]));
      x1 = fmaxf(x1, fmaxf(s2[4 * b + 2], s2[4 * b + 3]));
    }
    x0 = fmaxf(x0, __shfl_xor_sync(~0u, x0, 1)); x0 = fmaxf(x0, __shfl_xor_sync(~0u, x0, 2));
    x1 = fmaxf(x1, __shfl_xor_sync(~0u, x1, 1)); x1 = fmaxf(x1, __shfl_xor_sync(~0u, x1, 2));
    const float a0 = ex2f(m0 - x0), a1 = ex2f(m1 - x1);
    m0 = x0; m1 = x1;
#pragma unroll
    for (int b = 0; b < 3; b++) { o[4 * b] *= a0; o[4 * b + 1] *= a0; o[4 * b + 2] *= a1; o[4 * b + 3] *= a1; }
#pragma unroll
    for (int b = 0; b < 8; b++) {
      p2[2 * b] = pack_bf16(ex2f(s2[4 * b] - m0), ex2f(s2[4 * b + 1] - m0));
      p2[2 * b + 1] = pack_bf16(ex2f(s2[4 * b + 2] - m1), ex2f(s2[4 * b + 3] - m1));
    }
    const uint32_t vlo = desc_lo(kb + HB, 128);
    WG_FENCE();
#pragma unroll
    for (int kk = 0; kk < 4; kk++)
      wgmma_n24_rs_tb_acc(o, p2[4 * kk], p2[4 * kk + 1], p2[4 * kk + 2], p2[4 * kk + 3], vlo + kk * 16, VD_HI);
    WG_COMMIT();
    WG_WAIT(0);
    fence_regs(o);
    fence_regs_u(p2);
  }
}

constexpr int G3_SLOTS = 15;
constexpr int G3_XCH = G3_SLOTS * AT_KV;

__device__ __forceinline__ void g3_consumer(uint32_t sbase, uint8_t* sgen, uint32_t full, uint32_t empty, uint32_t xbar, uint32_t peerReady, int tid, int lane,
                                            int wg, int w4, int rank, int mt, int nt, const CUtensorMap* tmOut) {
  float acc[80];
  const uint32_t a_lo0 = desc_lo(sbase + wg * 1024, CHB), b_lo0 = desc_lo(sbase, 2048);
  constexpr uint32_t a_hi = desc_hi(128, 0), b_hi = desc_hi(512, 2);
  constexpr uint32_t T = AT_KV >> 4;
  {
    mbar_wait(full, 0);
    mbar_wait(full + 8, 0);
    WG_FENCE();
    mma_160<true>(acc, a_lo0 + T, a_hi, b_lo0, b_hi, 128);
    mma_160<false>(acc, a_lo0 + T + 256, a_hi, b_lo0 + 64, b_hi, 128);
    WG_COMMIT();
  }
  int sw = 2, pw = 0, pa = 1;
  uint32_t phw = 0;
#pragma unroll 1
  for (int ks = 1; ks < 20; ks++) {
    int sa = sw + 1; uint32_t pha = phw;
    if (sa == G3_SLOTS) { sa = 0; pha ^= 1; }
    mbar_wait(full + 8 * sw, phw);
    mbar_wait(full + 8 * sa, pha);
    WG_FENCE();
    mma_160<false>(acc, a_lo0 + sa * T, a_hi, b_lo0 + sw * T, b_hi, 128);
    mma_160<false>(acc, a_lo0 + sa * T + 256, a_hi, b_lo0 + sw * T + 64, b_hi, 128);
    WG_COMMIT();
    WG_WAIT(1);
    if (lane == 0) { mbar_arrive(empty + 8 * pw); mbar_arrive(empty + 8 * pa); }
    pw = sw; pa = sa;
    sw = sa + 1; phw = pha;
    if (sw == G3_SLOTS) { sw = 0; phw ^= 1; }
  }
  WG_WAIT(0);
  fence_regs(acc);
  mbar_wait(peerReady, 0);
  {
    const uint32_t rdst = mapa(sbase + G3_XCH + (uint32_t)tid * 16, rank ^ 1), rbar = mapa(xbar, rank ^ 1);
#pragma unroll
    for (int i = 0; i < 10; i++) {
      float a, b, cc, d;
      if (rank == 0) { a = acc[40 + 4 * i]; b = acc[41 + 4 * i]; cc = acc[42 + 4 * i]; d = acc[43 + 4 * i]; }
      else { a = acc[4 * i]; b = acc[4 * i + 1]; cc = acc[4 * i + 2]; d = acc[4 * i + 3]; }
      asm volatile("st.async.weak.shared::cluster.mbarrier::complete_tx::bytes.v4.f32 [%0], {%1,%2,%3,%4}, [%5];"
                   ::"r"(rdst + i * 4096), "f"(a), "f"(b), "f"(cc), "f"(d), "r"(rbar) : "memory");
    }
  }
  asm volatile("bar.sync 1, 256;" ::: "memory");
  mbar_wait(xbar, 0);
  uint8_t* stg = sgen + wg * 10240 + (w4 * 16 + (lane >> 2)) * 160 + (lane & 3) * 4;
#pragma unroll
  for (int i = 0; i < 10; i++) {
    float4 r = *reinterpret_cast<const float4*>(sgen + G3_XCH + tid * 16 + i * 4096);
    float a, b, cc, d;
    if (rank == 0) { a = acc[4 * i]; b = acc[4 * i + 1]; cc = acc[4 * i + 2]; d = acc[4 * i + 3]; }
    else { a = acc[40 + 4 * i]; b = acc[41 + 4 * i]; cc = acc[42 + 4 * i]; d = acc[43 + 4 * i]; }
    *reinterpret_cast<uint32_t*>(stg + 16 * i) = pack_bf16(a + r.x, b + r.y);
    *reinterpret_cast<uint32_t*>(stg + 8 * 160 + 16 * i) = pack_bf16(cc + r.z, d + r.w);
  }
  asm volatile("fence.proxy.async.shared::cta;" ::: "memory");
  asm volatile("bar.sync %0, 128;" ::"r"(2 + wg) : "memory");
  if ((tid & 127) == 0) {
    tma_store_2d(tmOut, sbase + wg * 10240, nt * 160 + rank * 80, mt * 128 + wg * 64);
    asm volatile("cp.async.bulk.commit_group;" ::: "memory");
    asm volatile("cp.async.bulk.wait_group.read 0;" ::: "memory");
  }
}

__device__ __forceinline__ int g1_tile_id(int j, int t) {
  int branch, idx;
  if (t == 0) { branch = 1; idx = j; }
  else if (t == 1) { if (j < 4) { branch = 1; idx = 8 + j; } else { branch = 0; idx = j; } }
  else { branch = 0; idx = j < 4 ? 8 + j : j - 4; }
  return branch * 16 + (2 - (idx >> 2)) * 4 + (idx & 3);
}
constexpr int BAR_OFF = 225280;
constexpr int MEGA_SMEM = BAR_OFF + 1280 + 4096 + 1024;

__device__ __forceinline__ void spin_ge(const unsigned* p, unsigned target) {
  unsigned v, n = 0;
  while (true) {
    asm volatile("ld.acquire.gpu.global.u32 %0, [%1];" : "=r"(v) : "l"(p) : "memory");
    if (v >= target) break;
    __nanosleep(40);
    if (++n > (1u << 24)) __trap();
  }
}
__device__ __forceinline__ void red_release(unsigned* p) {
  asm volatile("red.release.gpu.global.add.u32 [%0], 1;" ::"l"(p) : "memory");
}

__global__ void __cluster_dims__(2, 1, 1) __launch_bounds__(640, 1)
fused_kernel(const __grid_constant__ CUtensorMap tmX, const __grid_constant__ CUtensorMap tmWA, const __grid_constant__ CUtensorMap tmWB,
             const __grid_constant__ CUtensorMap tmKV, const __grid_constant__ CUtensorMap tmKVA, const __grid_constant__ CUtensorMap tmOC,
             const __grid_constant__ CUtensorMap tmWoA, const __grid_constant__ CUtensorMap tmWoB, const __grid_constant__ CUtensorMap tmOut,
             const __nv_bfloat16* __restrict__ xin, const __nv_bfloat16* __restrict__ gate_w) {
  extern __shared__ uint8_t smem_raw[];
  const uint32_t sbase = (smem_u32(smem_raw) + 1023) & ~1023u;
  uint8_t* sgen = smem_raw + (sbase - smem_u32(smem_raw));
  const uint32_t sBar = sbase + BAR_OFF;
  const uint32_t fullA = sBar, fullB = sBar + 80, emptyB = fullB + 48, order = emptyB + 48, tdone = order + 16, afree = sBar + 640;
  const uint32_t kvfull = sBar + 256, kvaFull = kvfull + 128, kvbReady = kvaFull + 16, go2 = kvbReady + 8, go2b = go2 + 8,
                 kvdone = go2b + 8, attdone = kvdone + 16, middone = attdone + 8, goQ = middone + 8;
  const uint32_t xbar = sBar + 512, peerReady = xbar + 8, full3 = sBar + 768, empty3 = full3 + 128, kvfree = sBar + 1024;
  const int tid = threadIdx.x, warp = __shfl_sync(~0u, tid >> 5, 0), lane = tid & 31;
  const int bid = blockIdx.x, rank = bid & 1;
  const int mt = (bid >> 4) * 2 + rank, j = (bid >> 1) & 7;
  const int h = bid >> 2, rb = bid & 3;
  const int mt3 = bid >> 3, nt = (bid >> 1) & 3;
  if (tid == 512) {
    for (int i = 0; i < G1_BST; i++) { mbar_init(fullB + 8 * i, 1); mbar_init(emptyB + 8 * i, 16); }
    mbar_init(order, 8); mbar_init(order + 8, 8);
    fence_barrier_init();
  } else if (tid == 544) {
    prefetch_tmap(&tmX); prefetch_tmap(&tmWB);
    for (int i = 0; i < 10; i++) mbar_init(fullA + 8 * i, 1);
    for (int i = 0; i < 3; i++) mbar_init(tdone + 8 * i, 8);
    for (int i = 0; i < 9; i++) mbar_init(afree + 8 * i, 8);
    fence_barrier_init();
  } else if (tid == 576) {
    for (int i = 0; i < 16; i++) mbar_init(kvfull + 8 * i, 1);
    fence_barrier_init();
  } else if (tid == 0) {
    for (int i = 0; i < G3_SLOTS; i++) { mbar_init(full3 + 8 * i, 1); mbar_init(empty3 + 8 * i, 8); }
    fence_barrier_init();
  } else if (tid == 32) {
    for (int i = 0; i < G3_SLOTS; i++) mbar_init(kvfree + 8 * i, 16);
    fence_barrier_init();
  } else if (tid == 608) {
    prefetch_tmap(&tmWA);
    mbar_init(kvaFull, 1); mbar_init(kvaFull + 8, 1); mbar_init(kvbReady, 1); mbar_init(go2, 1); mbar_init(go2b, 1); mbar_init(kvdone, 8); mbar_init(kvdone + 8, 8); mbar_init(attdone, 16);
    mbar_init(middone, 16); mbar_init(goQ, 1);
    mbar_init(xbar, 1); mbar_init(peerReady, 1);
    fence_barrier_init();
    mbar_expect_tx(xbar, 40960);
  }
  __syncwarp();
  cluster_arrive();
  cluster_wait();

  if (warp >= 16) {
    asm volatile("setmaxnreg.dec.sync.aligned.u32 32;");
    const int hw = warp - 16;
    if (hw < 3) {
      if (lane == 0) {
        const uint32_t sA = sbase, sB = sbase + G1_A_BYTES;
        for (int it = 0; it < 60; it++) {
          const int t = it / 20, kb = it - t * 20, s = it % G1_BST;
          if ((s % 3) != hw) continue;
          if (t == 0 && !(kb & 1)) {
            mbar_expect_tx(fullA + 8 * (kb >> 1), 16384);
            tma_load_2d(sA + (kb >> 1) * 16384, &tmX, kb * 32, mt * 128, fullA + 8 * (kb >> 1));
          }
          const int id = g1_tile_id(j, t);
          mbar_wait(emptyB + 8 * s, ((it / G1_BST) & 1) ^ 1);
          mbar_expect_tx(fullB + 8 * s, G1_B_BYTES);
          if (((it >> (it < 40 ? 1 : 0)) & 1) == rank) tma_load_3d_mc(sB + s * G1_B_BYTES, (id & 16) ? &tmWB : &tmWA, 0, kb * 32, (id & 15) * 5, fullB + 8 * s, 3);
        }
        if (hw == 0) {
          prefetch_tmap(&tmKVA);
          spin_ge(g_g1cnt + 4 + (h >> 3), 48);
          fence_proxy_async_gmem();
          mbar_wait(tdone + 16, 0);
          fence_proxy_async_smem();
          for (int i = 11; i < 16; i++) {
            mbar_expect_tx(kvfull + 8 * i, AT_KV);
            tma_load_2d(sbase + i * AT_KV, &tmKV, 0, (h * NMT + i) * 24, kvfull + 8 * i);
          }
          spin_ge(g_g1cnt + (h >> 3), 48);
          fence_proxy_async_gmem();
          mbar_expect_tx(kvaFull, 2 * AT_KV);
          tma_load_2d(sbase + KVA_OFF, &tmKVA, 0, (h * NMT + rb * 4 + 2) * 24, kvaFull);
          for (int i = 0; i < 8; i++) spin_ge(g_g1cnt + i, 48);
          mbar_arrive(go2b);
        }
        if (hw == 1) {
          const int id = g1_tile_id(j, 2);
          mbar_wait(tdone + 16, 0);
          red_release(g_g1cnt + (id >> 4) * 4 + (id & 3));
        }
        if (hw == 2) {
          mbar_wait(middone, 0);
          red_release(g_atcnt + 8 + rb * 2 + (h >> 4));
          mbar_wait(attdone, 0);
          mbar_arrive_remote(mapa(peerReady, rank ^ 1));
          red_release(g_atcnt + rb * 2 + (h >> 4));
        }
        if (hw < 2) {
          if (hw == 0) prefetch_tmap(&tmOC); else { prefetch_tmap(&tmWoA); prefetch_tmap(&tmWoB); }
          const int early = (mt3 >> 1) & 1, nearly = rank ? 2 : 3;
          if (hw == 0) {
            mbar_wait(middone, 0);
            spin_ge(g_atcnt + 8 + (mt3 >> 2) * 2, 16); spin_ge(g_atcnt + 8 + (mt3 >> 2) * 2 + 1, 16);
            fence_proxy_async_gmem();
          }
          for (int ks = 0; ks < 20; ks++) {
            const int kb = ks >> 1, br = kb >= 5, i5 = kb - 5;
            const int kq = 2 * (!br ? rank * 5 + kb : (i5 < nearly ? early * 5 + rank * 3 + i5 : (1 - early) * 5 + rank * 2 + i5 - nearly)) + (ks & 1);
            const int p = 2 * ks + (1 - hw), u = p / G3_SLOTS, s = p - u * G3_SLOTS;
            if (u == 0) { mbar_wait(kvfree + 8 * s, 0); fence_proxy_async_smem(); }
            else mbar_wait(empty3 + 8 * s, (u - 1) & 1);
            if (hw == 0) {
              if (ks == 10 + 2 * nearly) { spin_ge(g_atcnt + (mt3 >> 2) * 2 + 1 - early, 16); fence_proxy_async_gmem(); }
              mbar_expect_tx(full3 + 8 * s, 8192);
              tma_load_2d(sbase + s * AT_KV, &tmOC, 0, (mt3 * 160 + br * 80 + kq * 4) * 4, full3 + 8 * s);
            } else {
              mbar_expect_tx(full3 + 8 * s, 10240);
              tma_load_3d(sbase + s * AT_KV, br ? &tmWoB : &tmWoA, 0, kq * 32, nt * 5, full3 + 8 * s);
            }
          }
          if (hw == 0) {
            if (atomicAdd(&g_fin, 1u) == 127u) {
              for (int i = 0; i < 8; i++) g_g1cnt[i] = 0;
              for (int i = 0; i < 16; i++) g_atcnt[i] = 0;
              for (int i = 0; i < NH; i++) g_kvflag[i] = 0;
              g_fin = 0;
            }
          }
        }
      }
    } else {
      if (j < 4 && !(mt & 1)) {
        float4* z = reinterpret_cast<float4*>(g_kvpart + (j * 8 + (mt >> 1)) * 576);
        for (int i = lane; i < 144; i += 32) z[i] = make_float4(0.f, 0.f, 0.f, 0.f);
      }
      __syncwarp();
      if (lane == 0) {
        prefetch_tmap(&tmKV);
        for (int t = 0; t < 2; t++) {
          const int id = g1_tile_id(j, t);
          mbar_wait(tdone + 8 * t, 0);
          red_release(g_g1cnt + (id >> 4) * 4 + (id & 3));
        }
        spin_ge(g_g1cnt + 4 + (h >> 3), 48);
        mbar_arrive(goQ);
        fence_proxy_async_gmem();
        for (int i = 0; i < 11; i++) {
          mbar_wait(afree + 8 * ((AT_KV * (i + 1) - 1) >> 14), 0);
          fence_proxy_async_smem();
          mbar_expect_tx(kvfull + 8 * i, AT_KV);
          tma_load_2d(sbase + i * AT_KV, &tmKV, 0, (h * NMT + i) * 24, kvfull + 8 * i);
        }
        spin_ge(g_g1cnt + (h >> 3), 48);
        fence_proxy_async_gmem();
        mbar_wait(kvdone, 0);
        fence_proxy_async_smem();
        mbar_expect_tx(kvaFull + 8, 2 * AT_KV);
        tma_load_2d(sbase + KVA_OFF, &tmKVA, 0, (h * NMT + rb * 4) * 24, kvaFull + 8);
        mbar_wait(kvdone + 8, 0);
        red_release(g_kvflag + h);
        spin_ge(g_kvflag + h, 4);
      }
      __syncwarp();
#pragma unroll 1
      for (int i = 0; i < 12; i += 4) {
        float2 t[4];
#pragma unroll
        for (int u = 0; u < 4; u++) {
          const int pi = lane + 32 * (i + u);
          t[u] = make_float2(0.f, 0.f);
          if (pi < 288) t[u] = __ldcg(reinterpret_cast<const float2*>(g_kvpart + h * 576 + 2 * pi));
        }
#pragma unroll
        for (int u = 0; u < 4; u++) {
          const int pi = lane + 32 * (i + u), d = pi / 12, e = (pi - d * 12) * 2;
          *reinterpret_cast<uint32_t*>(sgen + 16 * AT_KV + (e >> 3) * 512 + d * 16 + (e & 7) * 2) = pack_bf16(t[u].x, t[u].y);
        }
      }
      fence_proxy_async_smem();
      __syncwarp();
      if (lane == 0) mbar_arrive(kvbReady);
    }
  } else {
    asm volatile("setmaxnreg.inc.sync.aligned.u32 112;");
    const int w4 = warp & 3;
    {
      const int grp = warp >> 3, wg = (warp >> 2) & 1;
      const uint32_t a_lo0 = desc_lo(sbase + wg * 8192, 16), b_lo0 = desc_lo(sbase + G1_A_BYTES, 2048);
      const uint32_t emptyR = mapa(emptyB, rank ^ 1);
      if (grp == 1) {
        const int row = mt * 128 + j * 16 + (warp - 8) * 2;
        const uint2* xp = reinterpret_cast<const uint2*>(xin + (size_t)row * DM);
        const uint2* gp = reinterpret_cast<const uint2*>(gate_w);
        float s0 = 0.f, s1 = 0.f;
#pragma unroll
        for (int i = 0; i < 5; i++) {
          uint2 a = __ldg(xp + lane + 32 * i), b = __ldg(xp + 160 + lane + 32 * i), gw = __ldg(gp + lane + 32 * i);
          s0 += bf_lo(a.x) * bf_lo(gw.x) + bf_hi(a.x) * bf_hi(gw.x) + bf_lo(a.y) * bf_lo(gw.y) + bf_hi(a.y) * bf_hi(gw.y);
          s1 += bf_lo(b.x) * bf_lo(gw.x) + bf_hi(b.x) * bf_hi(gw.x) + bf_lo(b.y) * bf_lo(gw.y) + bf_hi(b.y) * bf_hi(gw.y);
        }
#pragma unroll
        for (int o = 16; o >= 1; o >>= 1) { s0 += __shfl_xor_sync(~0u, s0, o); s1 += __shfl_xor_sync(~0u, s1, o); }
        if (lane == 0) { g_gate[row] = 1.0f / (1.0f + __expf(-s0)); g_gate[row + 1] = 1.0f / (1.0f + __expf(-s1)); }
      }
#pragma unroll 1
      for (int t = grp; t < 3; t += 2) {
        if (t > 0) mbar_wait(order + 8 * (t - 1), 0);
        const int id = g1_tile_id(j, t), branch = id >> 4, type = (id >> 2) & 3, h0 = (id & 3) * 8;
        const int row = wg * 64 + w4 * 16 + (lane >> 2);
        const int grp16 = mt * 8 + wg * 4 + w4;
        int kind; uint8_t* base; float* nrm;
        const size_t boff = (size_t)(h0 * NMT + mt) * 2 * HB;
        if (type == 0) {
          base = g_QP + boff + (branch ? 0 : HB);
          kind = branch ? 1 : 0; nrm = g_nrmQ + h0 * 128 + grp16;
        } else {
          base = (branch ? g_KVB : g_KVA) + boff + (type == 2 ? HB : 0);
          kind = type == 2 ? 3 : (branch ? 2 : 0); nrm = g_nrmK + h0 * 128 + grp16;
        }
        g1_tile(t, a_lo0, b_lo0, fullA, fullB, emptyB, order, lane, kind, base, row, nrm, emptyR, afree, (t == 1 && branch == 0) ? tdone : 0u);
        __syncwarp();
        if (lane == 0) mbar_arrive(tdone + 8 * t);
      }
    }
    {
      AttnCtx x;
      x.sKV = sbase; x.full = kvfull; x.kvaFull = kvaFull; x.kvdone = kvdone; x.kvfree = kvfree;
      x.h = h; x.wg = warp >> 2; x.w4 = w4; x.lane = lane;
      const uint32_t sKVB = sbase + 16 * AT_KV;
      const int hh = h >> 4;
      const int mt0 = rb * 4 + (x.wg >> 1) + 2 * hh, mt1 = rb * 4 + (x.wg >> 1) + 2 * (1 - hh);
      const int odd = h & 1;
      const int cA = odd, cB = odd ? 0 : 2;
      const int colA = h * 20 - 4 * odd;
      x.kA = cA * CHB; x.kB = cB * CHB;
      volatile uint32_t* park = reinterpret_cast<volatile uint32_t*>(sgen + BAR_OFF + 1280) + tid;
      bool fast;
      float o[12];
      {
        const int c = lane & 3, row = (x.wg & 1) * 64 + w4 * 16 + (lane >> 2);
        mbar_wait(goQ, 0);
        Frag6 q = load_frag(g_QP + (size_t)(h * NMT + mt0) * 2 * HB + row * 16 + c * 4, cA, cB);
        float kmax2, qmax2;
        const float qn0 = __ldcg(g_nrmQ + h * 128 + mt0 * 8 + (x.wg & 1) * 4 + w4), qn1 = __ldcg(g_nrmQ + h * 128 + mt1 * 8 + (x.wg & 1) * 4 + w4);
        {
          float4 kv4 = __ldcg(reinterpret_cast<const float4*>(g_nrmK + h * 128 + lane * 4));
          kmax2 = fmaxf(fmaxf(kv4.x, kv4.y), fmaxf(kv4.z, kv4.w));
          qmax2 = __ldcg(g_nrmQ + h * 128 + rb * 32 + lane);
#pragma unroll
          for (int of = 16; of >= 1; of >>= 1) {
            kmax2 = fmaxf(kmax2, __shfl_xor_sync(~0u, kmax2, of));
            qmax2 = fmaxf(qmax2, __shfl_xor_sync(~0u, qmax2, of));
          }
        }
        fast = __all_sync(~0u, sqrtf(qmax2 * kmax2) * 1.02f <= FAST_M_LIMIT);
        uint32_t bias0 = 0, bias1 = 0;
        if (fast) {
          const uint32_t mb0 = (__float_as_uint(sqrtf(qn0 * kmax2) * 1.01f) + 0xFFFFu) >> 16;
          const uint32_t mb1 = (__float_as_uint(sqrtf(qn1 * kmax2) * 1.01f) + 0xFFFFu) >> 16;
          bias0 = (c & 1) ? (mb0 | 0x3F808000u) : 0x3F803F80u;
          bias1 = (c & 1) ? (mb1 | 0x3F808000u) : 0x3F803F80u;
        }
        if (odd ? c < 2 : c >= 2) { q.b0 = bias0; q.b1 = bias0; }
        park[0] = bias1;
        if (fast) pass_fast<0>(x, q, o);
        else pass_slow(x, q, o, 0);
      }
      {
        int ln;
        asm volatile("mov.u32 %0, %%laneid;" : "=r"(ln));
        const int c = ln & 3, row = (x.wg & 1) * 64 + w4 * 16 + (ln >> 2);
        const uint32_t foff = row * 16 + c * 4;
        mbar_wait(go2b, 0);
        Frag6 q = load_frag(g_QP + (size_t)(h * NMT + mt1) * 2 * HB + foff, cA, cB);
        const Frag6 pa = load_frag(g_QP + (size_t)(h * NMT + mt0) * 2 * HB + HB + foff, 0, 2);
        const Frag6 pb = load_frag(g_QP + (size_t)(h * NMT + mt1) * 2 * HB + HB + foff, 0, 2);
        const float g00 = __ldcg(g_gate + mt0 * 128 + row), g01 = __ldcg(g_gate + mt0 * 128 + row + 8);
        const float g10 = __ldcg(g_gate + mt1 * 128 + row), g11 = __ldcg(g_gate + mt1 * 128 + row + 8);
        if (odd ? c < 2 : c >= 2) { q.b0 = park[0]; q.b1 = q.b0; }
        uint8_t* dst0 = g_OC + (size_t)mt0 * 160 * CHB + row * 16;
        uint8_t* dst1 = g_OC + (size_t)mt1 * 160 * CHB + row * 16;
        {
          float l0, l1;
          row_sums(o, ln, odd, l0, l1);
          store_o(o, __fdividef(1.0f - g00, l0), __fdividef(1.0f - g01, l1), dst0, 640 + colA, c, odd);
        }
        {
          float oa[12], ob[12];
          const uint32_t blo = desc_lo(sKVB, 128);
          constexpr uint32_t bhi = desc_hi(512, 0);
          mbar_wait(kvbReady, 0);
          WG_FENCE();
          wgmma_n24_rs_tb_init(oa, pa.a0, pa.a1, pa.a2, pa.a3, blo, bhi);
          wgmma_n24_rs_tb_acc(oa, pa.b0, pa.b1, 0u, 0u, blo + 16, bhi);
          wgmma_n24_rs_tb_init(ob, pb.a0, pb.a1, pb.a2, pb.a3, blo, bhi);
          wgmma_n24_rs_tb_acc(ob, pb.b0, pb.b1, 0u, 0u, blo + 16, bhi);
          WG_COMMIT();
          WG_WAIT(0);
          fence_regs(oa);
          fence_regs(ob);
          float d0, d1;
          row_sums(oa, ln, odd, d0, d1);
          store_o(oa, g00 / (d0 + 1e-6f), g01 / (d1 + 1e-6f), dst0, colA, c, odd);
          row_sums(ob, ln, odd, d0, d1);
          store_o(ob, g10 / (d0 + 1e-6f), g11 / (d1 + 1e-6f), dst1, colA, c, odd);
        }
        park[0] = __float_as_uint(1.0f - g10);
        park[512] = __float_as_uint(1.0f - g11);
        __syncwarp();
        if (ln == 0) mbar_arrive(middone);
        if (fast) pass_fast<1>(x, q, o);
        else {
          pass_slow(x, q, o, 1);
          if (ln == 0) for (int i = 0; i < G3_SLOTS; i++) mbar_arrive(kvfree + 8 * i);
        }
      }
      {
        int ln;
        asm volatile("mov.u32 %0, %%laneid;" : "=r"(ln));
        const int c = ln & 3, row = (x.wg & 1) * 64 + w4 * 16 + (ln >> 2);
        float l0, l1;
        row_sums(o, ln, odd, l0, l1);
        store_o(o, __fdividef(__uint_as_float(park[0]), l0), __fdividef(__uint_as_float(park[512]), l1),
                g_OC + (size_t)mt1 * 160 * CHB + row * 16, 640 + colA, c, odd);
        __syncwarp();
        if (ln == 0) mbar_arrive(attdone);
      }
    }
    if (warp >= 8) g3_consumer(sbase, sgen, full3, empty3, xbar, peerReady, tid - 256, lane, (warp >> 2) - 2, w4, rank, mt3, nt, &tmOut);
  }
}

typedef CUresult (*EncodeFn)(CUtensorMap*, CUtensorMapDataType, cuuint32_t, void*, const cuuint64_t*, const cuuint64_t*,
                             const cuuint32_t*, const cuuint32_t*, CUtensorMapInterleave, CUtensorMapSwizzle,
                             CUtensorMapL2promotion, CUtensorMapFloatOOBfill);

void make_map_2d(EncodeFn enc, CUtensorMap* tm, const void* p, uint64_t cols, uint64_t rows, uint32_t bc, uint32_t br, CUtensorMapSwizzle sw) {
  cuuint64_t dims[2] = {cols, rows};
  cuuint64_t strides[1] = {cols * 2};
  cuuint32_t box[2] = {bc, br};
  cuuint32_t es[2] = {1, 1};
  enc(tm, CU_TENSOR_MAP_DATA_TYPE_BFLOAT16, 2, const_cast<void*>(p), dims, strides, box, es, CU_TENSOR_MAP_INTERLEAVE_NONE, sw,
      CU_TENSOR_MAP_L2_PROMOTION_NONE, CU_TENSOR_MAP_FLOAT_OOB_FILL_NONE);
}

void make_w_map(EncodeFn enc, CUtensorMap* tm, const void* w, int ncols, int krows) {
  cuuint64_t dims[3] = {32, 640, (cuuint64_t)(ncols / 32)};
  cuuint64_t strides[2] = {(cuuint64_t)ncols * 2, 64};
  cuuint32_t box[3] = {32, (cuuint32_t)krows, 5};
  cuuint32_t es[3] = {1, 1, 1};
  enc(tm, CU_TENSOR_MAP_DATA_TYPE_BFLOAT16, 3, const_cast<void*>(w), dims, strides, box, es, CU_TENSOR_MAP_INTERLEAVE_NONE,
      CU_TENSOR_MAP_SWIZZLE_64B, CU_TENSOR_MAP_L2_PROMOTION_NONE, CU_TENSOR_MAP_FLOAT_OOB_FILL_NONE);
}

}

extern "C" void kernel_launch(void* const* d_in, const int* in_sizes, int n_in, void* d_out, int out_size) {
  const __nv_bfloat16* x = (const __nv_bfloat16*)d_in[0];
  const void* wqkvA = d_in[1];
  const void* woA = d_in[2];
  const void* wqkvB = d_in[4];
  const void* woB = d_in[5];
  const __nv_bfloat16* gate_w = (const __nv_bfloat16*)d_in[6];

  static EncodeFn enc = nullptr;
  if (!enc) {
    void* fn = nullptr;
    cudaDriverEntryPointQueryResult st;
    cudaGetDriverEntryPoint("cuTensorMapEncodeTiled", &fn, cudaEnableDefault, &st);
    enc = (EncodeFn)fn;
    cudaFuncSetAttribute(fused_kernel, cudaFuncAttributeMaxDynamicSharedMemorySize, MEGA_SMEM);
  }
  static void *pKVB = nullptr, *pKVA = nullptr, *pOC = nullptr;
  if (!pKVB) { cudaGetSymbolAddress(&pKVB, g_KVB); cudaGetSymbolAddress(&pKVA, g_KVA); cudaGetSymbolAddress(&pOC, g_OC); }
  CUtensorMap tmX, tmWA, tmWB, tmWoA, tmWoB, tmKV, tmKVA, tmOC, tmOut;
  make_map_2d(enc, &tmOut, d_out, 640, 2048, 80, 64, CU_TENSOR_MAP_SWIZZLE_NONE);
  make_map_2d(enc, &tmX, x, 640, 2048, 64, 128, CU_TENSOR_MAP_SWIZZLE_128B);
  make_w_map(enc, &tmWA, wqkvA, 1920, 32);
  make_w_map(enc, &tmWB, wqkvB, 1920, 32);
  make_w_map(enc, &tmWoA, woA, 640, 32);
  make_w_map(enc, &tmWoB, woB, 640, 32);
  make_map_2d(enc, &tmKV, pKVB, 256, NH * NMT * 24, 256, 24, CU_TENSOR_MAP_SWIZZLE_NONE);
  make_map_2d(enc, &tmKVA, pKVA, 256, NH * NMT * 24, 256, 48, CU_TENSOR_MAP_SWIZZLE_NONE);
  make_map_2d(enc, &tmOC, pOC, 256, NMT * 160 * 4, 256, 16, CU_TENSOR_MAP_SWIZZLE_NONE);

  cudaStream_t st = cudaStreamPerThread;
  fused_kernel<<<128, 640, MEGA_SMEM, st>>>(tmX, tmWA, tmWB, tmKV, tmKVA, tmOC, tmWoA, tmWoB, tmOut, x, gate_w);
}
```
